```python
import torch

def _softmax(x, axis=-1):
    return torch.softmax(x, dim=axis)
def _gelu(x):
    return torch.nn.functional.gelu(x, approximate="tanh")
def _silu(x):
    return torch.nn.functional.silu(x)
def _sigmoid(x):
    return torch.sigmoid(x)
def _layernorm(x, axis=-1, eps=1e-5):
    m = x.mean(dim=axis, keepdim=True)
    v = x.var(dim=axis, keepdim=True, unbiased=False)
    return (x - m) / torch.sqrt(v + eps)
def _scatter_add(tgt, idx, src, axis=0):
    return tgt.clone().index_add_(axis, idx, src)
def _segment_sum(src, seg, n):
    out = torch.zeros((n,) + src.shape[1:], dtype=src.dtype)
    return out.index_add_(0, seg, src)
def _pad(x, pw):
    flat = tuple(v for pair in reversed(pw) for v in pair)
    return torch.nn.functional.pad(x, flat)

kernel_name = 'sequential_preLN__spectral_gfnet__swiglu_ffn__prompt'

def setup_inputs():

    _w = (lambda a: (lambda t: t.to(torch.bfloat16) if t.is_floating_point() else t)(torch.as_tensor(a)))
    def _A_setup():
        B, S, D = 1, 2048, 512
        Df = D // 2 + 1
        return {
            "x": _w((lambda *s: torch.randn(*s, dtype=torch.bfloat16) * 0.05)(B, S, D)),
            "w_r": _w((lambda *s: torch.randn(*s, dtype=torch.bfloat16) * 0.4)(S, Df) * 0.02),
            "w_i": _w((lambda *s: torch.randn(*s, dtype=torch.bfloat16) * 0.4)(S, Df) * 0.02),
        }
    _A_in = _A_setup()

    def _B_setup():
        B, S, D, F = 1, 2048, 512, 1792
        return {
            "x": _w((lambda *s: torch.randn(*s, dtype=torch.bfloat16) * 0.05)(B, S, D)),
            "w_gate": _w((lambda *s: torch.randn(*s, dtype=torch.bfloat16) * 0.05)(D, F)),
            "w_up": _w((lambda *s: torch.randn(*s, dtype=torch.bfloat16) * 0.05)(D, F)),
            "w_down": _w((lambda *s: torch.randn(*s, dtype=torch.bfloat16) * 0.05)(F, D)),
        }
    _B_in = _B_setup()

    return {
        "A_x": _A_in["x"],
        "A_w_r": _A_in["w_r"],
        "A_w_i": _A_in["w_i"],
        "B_x": _B_in["x"],
        "B_w_gate": _B_in["w_gate"],
        "B_w_up": _B_in["w_up"],
        "B_w_down": _B_in["w_down"],
    }

def reference(A_x, A_w_r, A_w_i, B_x, B_w_gate, B_w_up, B_w_down):
    def _A_ref(x, w_r, w_i):
        B, S, D = x.shape
        X = (lambda x, axes=(-2,-1): torch.fft.rfft2(x.float(), dim=axes))(x, axes=(-2, -1))
        W = w_r + 1j * w_i
        X = X * W
        y = (lambda x, s, axes=(-2,-1): torch.fft.irfft2(x, s=s, dim=axes).to(torch.bfloat16))(X, (S, D), axes=(-2, -1))
        return y

    def _B_ref(x, w_gate, w_up, w_down):
        g = _silu(x @ w_gate)
        u = x @ w_up
        return (g * u) @ w_down

    x = A_x
    h = x + _A_ref(_layernorm(x, axis=-1), A_w_r, A_w_i)
    h2 = h + _B_ref(_layernorm(h, axis=-1), B_w_gate, B_w_up, B_w_down)
    return h2
```

```cpp
#include <cuda_runtime.h>
#include <cuda.h>
#include <cuda_bf16.h>
#include <cuda_fp16.h>
#include <stdint.h>

#define TIMING 0

namespace {

constexpr int S_ = 2048, D_ = 512, F_ = 1792, WCOLS = 257;
constexpr int NCTA = 128;
constexpr int NSLOT = 6, SLOT_BYTES = 16384;
constexpr int SM_A = 0;
constexpr int SM_RING = 131072;
constexpr int SM_BAR = SM_RING + NSLOT * SLOT_BYTES;
constexpr int SM_TOTAL = SM_BAR + 512;
constexpr int SMEM_BYTES = SM_TOTAL + 1024;
constexpr int B_FULL = 0, B_EMPTY = 6, B_AFULL = 12, B_PFREE = 20, B_ACT = 22, B_PART = 26, B_PST = 28, B_NUM = 34;

__device__ uint4 g_z1[NCTA * 1024];
__device__ uint4 g_z2[NCTA * 1024];
__device__ __nv_bfloat16 g_ln2[S_ * D_];
__device__ __nv_bfloat16 g_h[S_ * D_];
__device__ uint4 g_part[NCTA * 3 * 1024];
__device__ unsigned g_epoch;
__device__ unsigned g_cnt[2 * 32];
__device__ unsigned g_flagC[NCTA];
__device__ unsigned g_flagH[NCTA];
__device__ unsigned g_flagP[NCTA * 8];
#define TSTAMP(i)

struct Maps { CUtensorMap g4, u4, g3, u3, dn, a, h, o; };

__device__ __forceinline__ uint32_t s2u(const void* p) { return (uint32_t)__cvta_generic_to_shared(p); }
__device__ __forceinline__ void mbar_init(uint32_t a, int c) { asm volatile("mbarrier.init.shared::cta.b64 [%0], %1;" ::"r"(a), "r"(c) : "memory"); }
__device__ __forceinline__ void mbar_expect(uint32_t a, uint32_t b) { asm volatile("mbarrier.arrive.expect_tx.shared::cta.b64 _, [%0], %1;" ::"r"(a), "r"(b) : "memory"); }
__device__ __forceinline__ void mbar_arrive(uint32_t a) { asm volatile("mbarrier.arrive.shared::cta.b64 _, [%0];" ::"r"(a) : "memory"); }
__device__ __forceinline__ void mbar_arrive_remote(uint32_t a) { asm volatile("mbarrier.arrive.shared::cluster.b64 _, [%0];" ::"r"(a) : "memory"); }
__device__ __forceinline__ void mbar_wait(uint32_t a, uint32_t ph) {
  asm volatile("{\n.reg .pred p;\n.reg .u32 n;\nmov.u32 n, 0;\n"
               "L_w:\nmbarrier.try_wait.parity.shared::cta.b64 p, [%0], %1;\n@p bra L_d;\n"
               "add.u32 n, n, 1;\nsetp.lt.u32 p, n, 262144;\n@p bra L_w;\ntrap;\nL_d:\n}\n" ::"r"(a), "r"(ph) : "memory");
}
__device__ __forceinline__ void mbar_wait_cluster(uint32_t a, uint32_t ph) {
  asm volatile("{\n.reg .pred p;\n.reg .u32 n;\nmov.u32 n, 0;\n"
               "L_w:\nmbarrier.try_wait.parity.acquire.cluster.shared::cta.b64 p, [%0], %1;\n@p bra L_d;\n"
               "add.u32 n, n, 1;\nsetp.lt.u32 p, n, 262144;\n@p bra L_w;\ntrap;\nL_d:\n}\n" ::"r"(a), "r"(ph) : "memory");
}
__device__ __forceinline__ void spin_guard(int& it) {
  ++it;
  asm volatile("{\n.reg .pred p;\nsetp.gt.s32 p, %0, 1048576;\n@p trap;\n}\n" ::"r"(it));
}
__device__ __forceinline__ void bar_sync(int id, int n) { asm volatile("bar.sync %0, %1;" ::"r"(id), "r"(n) : "memory"); }
__device__ __forceinline__ void bar_arrive(int id, int n) { asm volatile("bar.arrive %0, %1;" ::"r"(id), "r"(n) : "memory"); }
__device__ __forceinline__ uint32_t mapa(uint32_t a, uint32_t r) { uint32_t o; asm volatile("mapa.shared::cluster.u32 %0, %1, %2;" : "=r"(o) : "r"(a), "r"(r)); return o; }
__device__ __forceinline__ void tma2d(uint32_t dst, const CUtensorMap* m, uint32_t bar, int c0, int c1) {
  asm volatile("cp.async.bulk.tensor.2d.shared::cluster.global.mbarrier::complete_tx::bytes [%0], [%1, {%3, %4}], [%2];"
               ::"r"(dst), "l"(m), "r"(bar), "r"(c0), "r"(c1) : "memory");
}
__device__ __forceinline__ void tma3d(uint32_t dst, const CUtensorMap* m, uint32_t bar, int c0, int c1, int c2) {
  asm volatile("cp.async.bulk.tensor.3d.shared::cluster.global.mbarrier::complete_tx::bytes [%0], [%1, {%3, %4, %5}], [%2];"
               ::"r"(dst), "l"(m), "r"(bar), "r"(c0), "r"(c1), "r"(c2) : "memory");
}
__device__ __forceinline__ void bulk_g2s(uint32_t dst, const void* src, uint32_t bytes, uint32_t bar) {
  asm volatile("cp.async.bulk.shared::cluster.global.mbarrier::complete_tx::bytes [%0], [%1], %2, [%3];"
               ::"r"(dst), "l"(src), "r"(bytes), "r"(bar) : "memory");
}
__device__ __forceinline__ unsigned ld_relaxed(const unsigned* p) { unsigned v; asm volatile("ld.relaxed.gpu.global.u32 %0, [%1];" : "=r"(v) : "l"(p) : "memory"); return v; }
__device__ __forceinline__ unsigned ld_acquire(const unsigned* p) { unsigned v; asm volatile("ld.acquire.gpu.global.u32 %0, [%1];" : "=r"(v) : "l"(p) : "memory"); return v; }
__device__ __forceinline__ void st_relaxed(unsigned* p, unsigned v) { asm volatile("st.relaxed.gpu.global.u32 [%0], %1;" ::"l"(p), "r"(v) : "memory"); }
__device__ __forceinline__ void red_add(unsigned* p, unsigned v) { asm volatile("red.relaxed.gpu.global.add.u32 [%0], %1;" ::"l"(p), "r"(v) : "memory"); }
__device__ __forceinline__ uint4 ldg_relaxed4(const uint4* p) {
  uint4 v; asm volatile("ld.relaxed.gpu.global.v4.u32 {%0,%1,%2,%3}, [%4];" : "=r"(v.x), "=r"(v.y), "=r"(v.z), "=r"(v.w) : "l"(p) : "memory"); return v;
}
__device__ __forceinline__ void stg_relaxed4(uint4* p, uint32_t a, uint32_t b, uint32_t c, uint32_t d) {
  asm volatile("st.relaxed.gpu.global.v4.u32 [%0], {%1,%2,%3,%4};" ::"l"(p), "r"(a), "r"(b), "r"(c), "r"(d) : "memory");
}
__device__ __forceinline__ void sts4(uint32_t a, uint32_t x, uint32_t y, uint32_t z, uint32_t w) {
  asm volatile("st.shared.v4.u32 [%0], {%1,%2,%3,%4};" ::"r"(a), "r"(x), "r"(y), "r"(z), "r"(w) : "memory");
}
__device__ __forceinline__ void lds4(uint32_t (&v)[4], uint32_t a) {
  asm volatile("ld.shared.v4.u32 {%0,%1,%2,%3}, [%4];" : "=r"(v[0]), "=r"(v[1]), "=r"(v[2]), "=r"(v[3]) : "r"(a) : "memory");
}
__device__ __forceinline__ uint32_t lds1(uint32_t a) { uint32_t v; asm volatile("ld.shared.u32 %0, [%1];" : "=r"(v) : "r"(a) : "memory"); return v; }
template <bool BF> __device__ __forceinline__ uint32_t pk(float lo, float hi) {
  uint32_t r;
  if (BF) asm("cvt.rn.bf16x2.f32 %0, %1, %2;" : "=r"(r) : "f"(hi), "f"(lo));
  else    asm("cvt.rn.f16x2.f32 %0, %1, %2;" : "=r"(r) : "f"(hi), "f"(lo));
  return r;
}
__device__ __forceinline__ float bf_lo(uint32_t v) { return __uint_as_float(v << 16); }
__device__ __forceinline__ float bf_hi(uint32_t v) { return __uint_as_float(v & 0xffff0000u); }
__device__ __forceinline__ float bf_round(float v) { return __uint_as_float(pk<true>(0.f, v) & 0xffff0000u); }
template <bool BF> __device__ __forceinline__ void mma16816(float (&d)[4], uint32_t a0, uint32_t a1, uint32_t a2, uint32_t a3, uint32_t b0, uint32_t b1) {
  if (BF) asm volatile("mma.sync.aligned.m16n8k16.row.col.f32.bf16.bf16.f32 {%0,%1,%2,%3}, {%4,%5,%6,%7}, {%8,%9}, {%0,%1,%2,%3};"
                       : "+f"(d[0]), "+f"(d[1]), "+f"(d[2]), "+f"(d[3]) : "r"(a0), "r"(a1), "r"(a2), "r"(a3), "r"(b0), "r"(b1));
  else    asm volatile("mma.sync.aligned.m16n8k16.row.col.f32.f16.f16.f32 {%0,%1,%2,%3}, {%4,%5,%6,%7}, {%8,%9}, {%0,%1,%2,%3};"
                       : "+f"(d[0]), "+f"(d[1]), "+f"(d[2]), "+f"(d[3]) : "r"(a0), "r"(a1), "r"(a2), "r"(a3), "r"(b0), "r"(b1));
}
template <int N> __device__ __forceinline__ void cexp(int m, float& co, float& si) {
  int q = ((m & (N - 1)) ^ (N / 2)) - N / 2;
  __sincosf((float)q * (6.283185307179586f / N), &si, &co);
}
template <bool BF, int N> __device__ __forceinline__ void aconst(int m, float sc, float imsign, uint32_t& re, uint32_t& im) {
  float co, si; cexp<N>(m, co, si); co *= sc; si *= sc;
  re = pk<BF>(co, -si * imsign); im = pk<BF>(si, co * imsign);
}
template <bool BF, int N> __device__ __forceinline__ uint32_t bconst(int m, float sc, int part, float outsign) {
  float co, si; cexp<N>(m, co, si); co *= sc; si *= sc;
  return part ? pk<BF>(si * outsign, co * outsign) : pk<BF>(co, -si);
}
__device__ __forceinline__ float warp_sum(float v) {
#pragma unroll
  for (int o = 16; o > 0; o >>= 1) v += __shfl_xor_sync(0xffffffffu, v, o);
  return v;
}

__device__ __forceinline__ void wgmma_ss_n256(float (&d)[128], uint64_t da, uint64_t db, int sd) {
  asm volatile("{\n.reg .pred p;\nsetp.ne.b32 p, %130, 0;\n"
    "wgmma.mma_async.sync.aligned.m64n256k16.f32.bf16.bf16 "
    "{%0, %1, %2, %3, %4, %5, %6, %7, %8, %9, %10, %11, %12, %13, %14, %15, %16, %17, %18, %19, %20, %21, "
    "%22, %23, %24, %25, %26, %27, %28, %29, %30, %31, %32, %33, %34, %35, %36, %37, %38, %39, %40, %41, "
    "%42, %43, %44, %45, %46, %47, %48, %49, %50, %51, %52, %53, %54, %55, %56, %57, %58, %59, %60, %61, "
    "%62, %63, %64, %65, %66, %67, %68, %69, %70, %71, %72, %73, %74, %75, %76, %77, %78, %79, %80, %81, "
    "%82, %83, %84, %85, %86, %87, %88, %89, %90, %91, %92, %93, %94, %95, %96, %97, %98, %99, %100, %101, "
    "%102, %103, %104, %105, %106, %107, %108, %109, %110, %111, %112, %113, %114, %115, %116, %117, %118, "
    "%119, %120, %121, %122, %123, %124, %125, %126, %127}, %128, %129, p, 1, 1, 0, 1;\n}\n"
    : "+f"(d[0]), "+f"(d[1]), "+f"(d[2]), "+f"(d[3]), "+f"(d[4]), "+f"(d[5]), "+f"(d[6]), "+f"(d[7]),
      "+f"(d[8]), "+f"(d[9]), "+f"(d[10]), "+f"(d[11]), "+f"(d[12]), "+f"(d[13]), "+f"(d[14]), "+f"(d[15]),
      "+f"(d[16]), "+f"(d[17]), "+f"(d[18]), "+f"(d[19]), "+f"(d[20]), "+f"(d[21]), "+f"(d[22]), "+f"(d[23]),
      "+f"(d[24]), "+f"(d[25]), "+f"(d[26]), "+f"(d[27]), "+f"(d[28]), "+f"(d[29]), "+f"(d[30]), "+f"(d[31]),
      "+f"(d[32]), "+f"(d[33]), "+f"(d[34]), "+f"(d[35]), "+f"(d[36]), "+f"(d[37]), "+f"(d[38]), "+f"(d[39]),
      "+f"(d[40]), "+f"(d[41]), "+f"(d[42]), "+f"(d[43]), "+f"(d[44]), "+f"(d[45]), "+f"(d[46]), "+f"(d[47]),
      "+f"(d[48]), "+f"(d[49]), "+f"(d[50]), "+f"(d[51]), "+f"(d[52]), "+f"(d[53]), "+f"(d[54]), "+f"(d[55]),
      "+f"(d[56]), "+f"(d[57]), "+f"(d[58]), "+f"(d[59]), "+f"(d[60]), "+f"(d[61]), "+f"(d[62]), "+f"(d[63]),
      "+f"(d[64]), "+f"(d[65]), "+f"(d[66]), "+f"(d[67]), "+f"(d[68]), "+f"(d[69]), "+f"(d[70]), "+f"(d[71]),
      "+f"(d[72]), "+f"(d[73]), "+f"(d[74]), "+f"(d[75]), "+f"(d[76]), "+f"(d[77]), "+f"(d[78]), "+f"(d[79]),
      "+f"(d[80]), "+f"(d[81]), "+f"(d[82]), "+f"(d[83]), "+f"(d[84]), "+f"(d[85]), "+f"(d[86]), "+f"(d[87]),
      "+f"(d[88]), "+f"(d[89]), "+f"(d[90]), "+f"(d[91]), "+f"(d[92]), "+f"(d[93]), "+f"(d[94]), "+f"(d[95]),
      "+f"(d[96]), "+f"(d[97]), "+f"(d[98]), "+f"(d[99]), "+f"(d[100]), "+f"(d[101]), "+f"(d[102]), "+f"(d[103]),
      "+f"(d[104]), "+f"(d[105]), "+f"(d[106]), "+f"(d[107]), "+f"(d[108]), "+f"(d[109]), "+f"(d[110]), "+f"(d[111]),
      "+f"(d[112]), "+f"(d[113]), "+f"(d[114]), "+f"(d[115]), "+f"(d[116]), "+f"(d[117]), "+f"(d[118]), "+f"(d[119]),
      "+f"(d[120]), "+f"(d[121]), "+f"(d[122]), "+f"(d[123]), "+f"(d[124]), "+f"(d[125]), "+f"(d[126]), "+f"(d[127])
    : "l"(da), "l"(db), "r"(sd));
}
__device__ __forceinline__ void wgmma_ss_n192(float (&d)[96], uint64_t da, uint64_t db, int sd) {
  asm volatile("{\n.reg .pred p;\nsetp.ne.b32 p, %98, 0;\n"
    "wgmma.mma_async.sync.aligned.m64n192k16.f32.bf16.bf16 "
    "{%0, %1, %2, %3, %4, %5, %6, %7, %8, %9, %10, %11, %12, %13, %14, %15, %16, %17, %18, %19, %20, %21, "
    "%22, %23, %24, %25, %26, %27, %28, %29, %30, %31, %32, %33, %34, %35, %36, %37, %38, %39, %40, %41, "
    "%42, %43, %44, %45, %46, %47, %48, %49, %50, %51, %52, %53, %54, %55, %56, %57, %58, %59, %60, %61, "
    "%62, %63, %64, %65, %66, %67, %68, %69, %70, %71, %72, %73, %74, %75, %76, %77, %78, %79, %80, %81, "
    "%82, %83, %84, %85, %86, %87, %88, %89, %90, %91, %92, %93, %94, %95}, %96, %97, p, 1, 1, 0, 1;\n}\n"
    : "+f"(d[0]), "+f"(d[1]), "+f"(d[2]), "+f"(d[3]), "+f"(d[4]), "+f"(d[5]), "+f"(d[6]), "+f"(d[7]),
      "+f"(d[8]), "+f"(d[9]), "+f"(d[10]), "+f"(d[11]), "+f"(d[12]), "+f"(d[13]), "+f"(d[14]), "+f"(d[15]),
      "+f"(d[16]), "+f"(d[17]), "+f"(d[18]), "+f"(d[19]), "+f"(d[20]), "+f"(d[21]), "+f"(d[22]), "+f"(d[23]),
      "+f"(d[24]), "+f"(d[25]), "+f"(d[26]), "+f"(d[27]), "+f"(d[28]), "+f"(d[29]), "+f"(d[30]), "+f"(d[31]),
      "+f"(d[32]), "+f"(d[33]), "+f"(d[34]), "+f"(d[35]), "+f"(d[36]), "+f"(d[37]), "+f"(d[38]), "+f"(d[39]),
      "+f"(d[40]), "+f"(d[41]), "+f"(d[42]), "+f"(d[43]), "+f"(d[44]), "+f"(d[45]), "+f"(d[46]), "+f"(d[47]),
      "+f"(d[48]), "+f"(d[49]), "+f"(d[50]), "+f"(d[51]), "+f"(d[52]), "+f"(d[53]), "+f"(d[54]), "+f"(d[55]),
      "+f"(d[56]), "+f"(d[57]), "+f"(d[58]), "+f"(d[59]), "+f"(d[60]), "+f"(d[61]), "+f"(d[62]), "+f"(d[63]),
      "+f"(d[64]), "+f"(d[65]), "+f"(d[66]), "+f"(d[67]), "+f"(d[68]), "+f"(d[69]), "+f"(d[70]), "+f"(d[71]),
      "+f"(d[72]), "+f"(d[73]), "+f"(d[74]), "+f"(d[75]), "+f"(d[76]), "+f"(d[77]), "+f"(d[78]), "+f"(d[79]),
      "+f"(d[80]), "+f"(d[81]), "+f"(d[82]), "+f"(d[83]), "+f"(d[84]), "+f"(d[85]), "+f"(d[86]), "+f"(d[87]),
      "+f"(d[88]), "+f"(d[89]), "+f"(d[90]), "+f"(d[91]), "+f"(d[92]), "+f"(d[93]), "+f"(d[94]), "+f"(d[95])
    : "l"(da), "l"(db), "r"(sd));
}
__device__ __forceinline__ void wgmma_rs_n64(float (&d)[32], uint32_t a0, uint32_t a1, uint32_t a2, uint32_t a3, uint64_t db, int sd) {
  asm volatile("{\n.reg .pred p;\nsetp.ne.b32 p, %37, 0;\n"
    "wgmma.mma_async.sync.aligned.m64n64k16.f32.bf16.bf16 "
    "{%0, %1, %2, %3, %4, %5, %6, %7, %8, %9, %10, %11, %12, %13, %14, %15, %16, %17, %18, %19, %20, %21, "
    "%22, %23, %24, %25, %26, %27, %28, %29, %30, %31}, {%32, %33, %34, %35}, %36, p, 1, 1, 1;\n}\n"
    : "+f"(d[0]), "+f"(d[1]), "+f"(d[2]), "+f"(d[3]), "+f"(d[4]), "+f"(d[5]), "+f"(d[6]), "+f"(d[7]),
      "+f"(d[8]), "+f"(d[9]), "+f"(d[10]), "+f"(d[11]), "+f"(d[12]), "+f"(d[13]), "+f"(d[14]), "+f"(d[15]),
      "+f"(d[16]), "+f"(d[17]), "+f"(d[18]), "+f"(d[19]), "+f"(d[20]), "+f"(d[21]), "+f"(d[22]), "+f"(d[23]),
      "+f"(d[24]), "+f"(d[25]), "+f"(d[26]), "+f"(d[27]), "+f"(d[28]), "+f"(d[29]), "+f"(d[30]), "+f"(d[31])
    : "r"(a0), "r"(a1), "r"(a2), "r"(a3), "l"(db), "r"(sd));
}

__device__ __forceinline__ void wg_fence() { asm volatile("wgmma.fence.sync.aligned;" ::: "memory"); }
__device__ __forceinline__ void wg_commit() { asm volatile("wgmma.commit_group.sync.aligned;" ::: "memory"); }
template <int N> __device__ __forceinline__ void wg_wait() { asm volatile("wgmma.wait_group.sync.aligned %0;" ::"n"(N) : "memory"); }
template <int N> __device__ __forceinline__ void reg_fence(float (&d)[N]) {
#pragma unroll
  for (int i = 0; i < N; i++) asm volatile("" : "+f"(d[i])::"memory");
}
__device__ __forceinline__ uint64_t mkdesc(uint32_t addr, uint32_t lbo, uint32_t sbo, uint32_t mode) {
  return (uint64_t)((addr & 0x3FFFF) >> 4) | ((uint64_t)(lbo >> 4) << 16) | ((uint64_t)(sbo >> 4) << 32) | ((uint64_t)mode << 62);
}
__device__ __forceinline__ float silu_mul(float g, float u) {
  float hgt = 0.5f * g, t;
  asm("tanh.approx.f32 %0, %1;" : "=f"(t) : "f"(hgt));
  return fmaf(hgt, t, hgt) * u;
}

constexpr bool INV_BF = true;

template <bool BF> __device__ __forceinline__ void stage_dataB(float (&T)[4][2][4], const uint32_t (&A)[2][2][4], const uint32_t (&in)[4][4]) {
#pragma unroll
  for (int e = 0; e < 4; e++)
#pragma unroll
    for (int p = 0; p < 2; p++) {
#pragma unroll
      for (int x = 0; x < 4; x++) T[e][p][x] = 0.f;
#pragma unroll
      for (int t = 0; t < 2; t++) mma16816<BF>(T[e][p], A[p][t][0], A[p][t][1], A[p][t][2], A[p][t][3], in[2 * t][e], in[2 * t + 1][e]);
    }
}
template <bool BF> __device__ __forceinline__ void stage_dataA(float (&O)[2][4][4], const uint32_t (&B)[4][2][2], const uint32_t (&L)[4][4]) {
#pragma unroll
  for (int tau = 0; tau < 2; tau++)
#pragma unroll
    for (int v = 0; v < 4; v++) {
#pragma unroll
      for (int x = 0; x < 4; x++) O[tau][v][x] = 0.f;
#pragma unroll
      for (int t = 0; t < 2; t++)
        mma16816<BF>(O[tau][v], L[2 * t][2 * tau], L[2 * t][2 * tau + 1], L[2 * t + 1][2 * tau], L[2 * t + 1][2 * tau + 1], B[v][t][0], B[v][t][1]);
    }
}
template <bool BF> __device__ __forceinline__ void fft256(float (&O)[4][4], const uint32_t (&z)[4][2], const uint32_t (&A1)[2][2][4],
                                                          const float (&tw)[2][4][2], const uint32_t (&B2)[4][2][2]) {
  uint32_t a[2][4];
#pragma unroll
  for (int uu = 0; uu < 2; uu++) {
    float T[2][4];
#pragma unroll
    for (int p = 0; p < 2; p++) {
#pragma unroll
      for (int x = 0; x < 4; x++) T[p][x] = 0.f;
#pragma unroll
      for (int t = 0; t < 2; t++) mma16816<BF>(T[p], A1[p][t][0], A1[p][t][1], A1[p][t][2], A1[p][t][3], z[2 * t][uu], z[2 * t + 1][uu]);
    }
#pragma unroll
    for (int x = 0; x < 4; x++) {
      float re = T[0][x] * tw[uu][x][0] - T[1][x] * tw[uu][x][1];
      float im = T[0][x] * tw[uu][x][1] + T[1][x] * tw[uu][x][0];
      a[uu][x] = pk<BF>(re, im);
    }
  }
#pragma unroll
  for (int v = 0; v < 4; v++) {
#pragma unroll
    for (int x = 0; x < 4; x++) O[v][x] = 0.f;
#pragma unroll
    for (int uu = 0; uu < 2; uu++) mma16816<BF>(O[v], a[uu][0], a[uu][2], a[uu][1], a[uu][3], B2[v][uu][0], B2[v][uu][1]);
  }
}
__device__ __forceinline__ int k2map(int v, int j) { return (v & 1) ? (15 - j - 2 * (v - 1)) : (j + 2 * v); }
__device__ __forceinline__ int rmap(int half, int c) { return half ? (c ? 16 - c : 8) : c; }

__device__ __forceinline__ void load_tagged(uint32_t (&in)[4][4], const uint4* base, int stride, uint32_t tag) {
  int it = 0;
  while (true) {
    uint4 v[4];
#pragma unroll
    for (int i = 0; i < 4; i++) v[i] = ldg_relaxed4(base + i * stride);
    uint32_t bad = ((v[0].x ^ tag) | (v[1].x ^ tag) | (v[2].x ^ tag) | (v[3].x ^ tag)) & 1u;
#pragma unroll
    for (int i = 0; i < 4; i++) { in[i][0] = v[i].x & ~1u; in[i][1] = v[i].y; in[i][2] = v[i].z; in[i][3] = v[i].w; }
    if (!__any_sync(0xffffffffu, bad)) break;
    spin_guard(it);
  }
}

__global__ void __cluster_dims__(2, 1, 1) __launch_bounds__(384, 1)
fused_kernel(const __grid_constant__ Maps maps, const __nv_bfloat16* __restrict__ x, const unsigned short* __restrict__ wr,
             const unsigned short* __restrict__ wi, const char* __restrict__ wgate, const char* __restrict__ wup, const char* __restrict__ wdown) {
  extern __shared__ uint8_t smem_raw[];
  const uint32_t sb = (s2u(smem_raw) + 1023u) & ~1023u;
  const uint32_t bar = sb + SM_BAR;
  const int tid = threadIdx.x, warp = tid >> 5, lane = tid & 31;
  const int b = blockIdx.x;
  const int mblk = b >> 3, jF = b & 7, r4 = jF >> 1, e_ = jF & 1;

  if (warp >= 8) {
    asm volatile("setmaxnreg.dec.sync.aligned.u32 40;");
    if (warp == 8 && lane == 0) {
      for (int i = 0; i < NSLOT; i++) { mbar_init(bar + 8 * (B_FULL + i), 1); mbar_init(bar + 8 * (B_EMPTY + i), 8); }
      for (int i = 0; i < 8; i++) mbar_init(bar + 8 * (B_AFULL + i), 1);
      for (int i = 0; i < 2; i++) { mbar_init(bar + 8 * (B_PFREE + i), 4); mbar_init(bar + 8 * (B_PART + i), 1); }
      for (int i = 0; i < 4; i++) mbar_init(bar + 8 * (B_ACT + i), 1);
      for (int i = 0; i < 6; i++) mbar_init(bar + 8 * (B_PST + i), 4);
      asm volatile("fence.mbarrier_init.release.cluster;" ::: "memory");
      mbar_expect(bar + 8 * (B_ACT + 0), 16384); mbar_expect(bar + 8 * (B_ACT + 1), 12288);
      mbar_expect(bar + 8 * (B_ACT + 2), 16384); mbar_expect(bar + 8 * (B_ACT + 3), 12288);
    }
    __syncwarp();
    asm volatile("barrier.cluster.arrive.release.aligned;" ::: "memory");
    asm volatile("barrier.cluster.wait.acquire.aligned;" ::: "memory");
    if (warp == 8) {
      bar_sync(4, 288);
      if (lane == 0) {
        const uint32_t pf = 3 * 512 * F_ * 2 / 3 / NCTA;
        asm volatile("cp.async.bulk.prefetch.L2.global [%0], %1;" ::"l"(wgate + (size_t)b * pf), "r"(pf) : "memory");
        asm volatile("cp.async.bulk.prefetch.L2.global [%0], %1;" ::"l"(wup + (size_t)b * pf), "r"(pf) : "memory");
        asm volatile("cp.async.bulk.prefetch.L2.global [%0], %1;" ::"l"(wdown + (size_t)b * pf), "r"(pf) : "memory");
        int slot = 0; uint32_t ph = 1;
        const int g0 = jF * 7;
#pragma unroll 1
        for (int st = 0; st < 48; st++) {
          const uint32_t dst = sb + SM_RING + slot * SLOT_BYTES, fb = bar + 8 * (B_FULL + slot);
          mbar_wait(bar + 8 * (B_EMPTY + slot), ph);
          if (st < 16) {
            mbar_expect(fb, 16384);
            tma3d(dst, &maps.g4, fb, 0, st * 32, g0);
            tma3d(dst + 8192, &maps.u4, fb, 0, st * 32, g0);
          } else if (st < 32) {
            mbar_expect(fb, 12288);
            tma3d(dst, &maps.g3, fb, 0, (st - 16) * 32, g0 + 4);
            tma3d(dst + 6144, &maps.u3, fb, 0, (st - 16) * 32, g0 + 4);
          } else {
            const int t = (st - 32) >> 2, qq = st & 3;
            const int q = (r4 + 1 + t) & 3;
            mbar_expect(fb, 14336);
            tma2d(dst, &maps.dn, fb, e_ * 256 + q * 64, r4 * 448 + (((qq >> 1) ^ e_) * 224) + (qq & 1) * 112);
          }
          if (++slot == NSLOT) { slot = 0; ph ^= 1; }
        }
      }
    } else if (warp == 9) {
      const unsigned ep = ld_relaxed(&g_epoch) + 1;
#pragma unroll 1
      for (int xch = 0; xch < 2; xch++) {
        if (lane == 0) {
          int it = 0;
          while ((int)(ld_relaxed(&g_cnt[xch * 32]) - ep * NCTA) < 0) spin_guard(it);
        }
        __syncwarp();
        bar_arrive(2, 288);
        if (xch == 1 && b == 0 && lane == 0) st_relaxed(&g_epoch, ep);
      }
      bar_sync(3, 288);
      if (lane == 0) { __threadfence(); st_relaxed(&g_flagC[b], ep); }
      {
        int it = 0;
        while (__any_sync(0xffffffffu, ld_acquire(&g_flagC[mblk * 8 + (lane & 7)]) != ep)) spin_guard(it);
      }
      asm volatile("fence.proxy.async;" ::: "memory");
      if (lane < 8) {
        mbar_expect(bar + 8 * (B_AFULL + lane), 16384);
        tma2d(sb + SM_A + lane * 16384, &maps.a, bar + 8 * (B_AFULL + lane), lane * 64, mblk * 128);
      }
      __syncwarp();
      bar_sync(5, 288);
      if (lane < 2) mbar_expect(bar + 8 * (B_PART + lane), 4 * 8192);
      __syncwarp();
      {
        int it = 0;
        while (__any_sync(0xffffffffu, ld_acquire(&g_flagH[mblk * 8 + (lane & 7)]) != ep)) spin_guard(it);
      }
      asm volatile("fence.proxy.async;" ::: "memory");
      if (lane < 2) tma2d(sb + SM_A + 7 * 16384 + lane * 8192, &maps.h, bar + 8 * (B_PART + lane), e_ * 256 + r4 * 64, mblk * 128 + lane * 64);
      if (lane < 2) {
#pragma unroll 1
        for (int t = 0; t < 3; t++) {
          int it = 0;
          while (ld_acquire(&g_flagP[b * 8 + t * 2 + lane]) != ep) spin_guard(it);
          asm volatile("fence.proxy.async;" ::: "memory");
          bulk_g2s(sb + SM_A + (4 + t) * 16384 + lane * 8192, &g_part[(b * 3 + t) * 1024 + lane * 512], 8192, bar + 8 * (B_PART + lane));
        }
      }
    } else {
      const int g = warp - 10;
      if (g == 0) {
        bar_sync(10, 288);
        if (lane == 0) { __threadfence(); st_relaxed(&g_flagH[b], lds1(bar + 8 * B_NUM)); }
      }
#pragma unroll 1
      for (int t = 0; t < 3; t++) {
        mbar_wait(bar + 8 * (B_PST + t * 2 + g), 0);
        const int q = (r4 + 1 + t) & 3;
        if (lane == 0) { __threadfence(); st_relaxed(&g_flagP[(mblk * 8 + q * 2 + e_) * 8 + t * 2 + g], lds1(bar + 8 * B_NUM)); }
      }
    }
  } else {
    asm volatile("setmaxnreg.inc.sync.aligned.u32 232;");
    const int w = warp, c = lane >> 2, j = lane & 3, jj = c >> 1, part = c & 1;
    uint2 xr[2][4];
#pragma unroll
    for (int u = 0; u < 2; u++)
#pragma unroll
      for (int i = 0; i < 4; i++)
        xr[u][i] = __ldg(reinterpret_cast<const uint2*>(x + (size_t)(128 * (2 * w + u) + b) * D_ + 32 * (4 * i + j) + 4 * c));
    const unsigned ep = ld_relaxed(&g_epoch) + 1;
    const int k1B = b >> 3, pgB = b & 7;
    unsigned short wraw[2][2][2][4];
    unsigned short wsp[2][2][2];
    const bool special = (pgB == 0 && c == 0);
#pragma unroll
    for (int y = 0; y < 2; y++)
#pragma unroll
      for (int v = 0; v < 2; v++) {
        const int sp = k1B + 16 * (2 * w + y) + 256 * (4 * v + j), sn = (S_ - sp) & (S_ - 1);
#pragma unroll
        for (int tau = 0; tau < 2; tau++) {
          const int p = 16 * pgB + rmap(tau, c);
          const int p1 = (p == 0) ? 256 : p;
          wraw[y][tau][v][0] = __ldg(wr + sp * WCOLS + p1);
          wraw[y][tau][v][1] = __ldg(wi + sp * WCOLS + p1);
          wraw[y][tau][v][2] = __ldg(wr + sn * WCOLS + 256 - p);
          wraw[y][tau][v][3] = __ldg(wi + sn * WCOLS + 256 - p);
        }
        wsp[y][v][0] = 0; wsp[y][v][1] = 0;
        if (special) { wsp[y][v][0] = __ldg(wr + sp * WCOLS + 128); wsp[y][v][1] = __ldg(wi + sp * WCOLS + 128); }
      }
    asm volatile("barrier.cluster.arrive.relaxed.aligned;" ::: "memory");

    const uint32_t tag = ep & 1u;
    if (tid == 0) asm volatile("st.shared.u32 [%0], %1;" ::"r"(bar + 8 * B_NUM), "r"(ep) : "memory");
    const uint32_t E0 = sb + SM_A, E1 = sb + SM_A + 32768;
    {
      uint32_t A1[2][2][4], B2[4][2][2], BC[4][2][2];
      float tw[2][4][2];
#pragma unroll
      for (int t = 0; t < 2; t++)
#pragma unroll
        for (int x = 0; x < 4; x++) aconst<false, 16>(-(rmap(x & 1, c) * (8 * t + 4 * (x >> 1) + j)), 0.25f, 1.f, A1[0][t][x], A1[1][t][x]);
#pragma unroll
      for (int uu = 0; uu < 2; uu++)
#pragma unroll
        for (int x = 0; x < 4; x++) cexp<256>(-(rmap(x >> 1, c) * (4 * j + 2 * (x & 1) + uu)), tw[uu][x][0], tw[uu][x][1]);
#pragma unroll
      for (int v = 0; v < 4; v++)
#pragma unroll
        for (int t = 0; t < 2; t++)
#pragma unroll
          for (int q = 0; q < 2; q++) {
            B2[v][t][q] = bconst<false, 16>(-((4 * j + 2 * q + t) * k2map(v, jj)), 0.25f, part, (v & 1) ? -1.f : 1.f);
            BC[v][t][q] = bconst<false, 2048>(-((4 * v + jj) * (128 * (8 * t + 4 * q + j) + b)), 0.25f, part, 1.f);
          }
      TSTAMP(0);
      float d[2][16], s1[2], s2[2];
#pragma unroll
      for (int u = 0; u < 2; u++) {
        s1[u] = 0.f;
#pragma unroll
        for (int i = 0; i < 4; i++) {
          d[u][4 * i + 0] = bf_lo(xr[u][i].x); d[u][4 * i + 1] = bf_hi(xr[u][i].x);
          d[u][4 * i + 2] = bf_lo(xr[u][i].y); d[u][4 * i + 3] = bf_hi(xr[u][i].y);
          s1[u] += (d[u][4 * i] + d[u][4 * i + 1]) + (d[u][4 * i + 2] + d[u][4 * i + 3]);
        }
      }
      TSTAMP(1);
#pragma unroll
      for (int o = 16; o > 0; o >>= 1) { s1[0] += __shfl_xor_sync(~0u, s1[0], o); s1[1] += __shfl_xor_sync(~0u, s1[1], o); }
#pragma unroll
      for (int u = 0; u < 2; u++) {
        const float mean = s1[u] * (1.f / D_);
        s2[u] = 0.f;
#pragma unroll
        for (int i = 0; i < 16; i++) { d[u][i] -= mean; s2[u] = fmaf(d[u][i], d[u][i], s2[u]); }
      }
#pragma unroll
      for (int o = 16; o > 0; o >>= 1) { s2[0] += __shfl_xor_sync(~0u, s2[0], o); s2[1] += __shfl_xor_sync(~0u, s2[1], o); }
#pragma unroll
      for (int u = 0; u < 2; u++) {
        const float rstd = rsqrtf(s2[u] * (1.f / D_) + 1e-5f);
        uint32_t z[4][2];
#pragma unroll
        for (int i = 0; i < 4; i++)
#pragma unroll
          for (int uu = 0; uu < 2; uu++) z[i][uu] = pk<false>(d[u][4 * i + 2 * uu] * rstd, d[u][4 * i + 2 * uu + 1] * rstd);
        float O[4][4];
        fft256<false>(O, z, A1, tw, B2);
        uint32_t qv[2], ov[2], tv[2];
#pragma unroll
        for (int g = 0; g < 2; g++) {
          qv[g] = pk<false>(O[2 * g + 1][0], O[2 * g + 1][1]);
          ov[g] = pk<false>(O[2 * g + 1][2], O[2 * g + 1][3]);
          tv[g] = __shfl_sync(~0u, qv[g], (lane & ~3) | ((lane - 1) & 3));
        }
#pragma unroll
        for (int g = 0; g < 2; g++) {
          const uint32_t e1 = c ? ov[g] : (j ? tv[g] : tv[g ^ 1]);
          const uint32_t e3 = c ? qv[g] : ov[g];
          sts4(E0 + (2 * w + u) * 1056 + (j + 4 * g) * 128 + ((c ^ (2 * j)) << 4),
               pk<false>(O[2 * g][0], O[2 * g][1]), e1, pk<false>(O[2 * g][2], O[2 * g][3]), e3);
        }
      }
      bar_sync(1, 256);
      uint32_t L[4][4];
#pragma unroll
      for (int q = 0; q < 4; q++) lds4(L[q], E0 + (j + 4 * q) * 1056 + w * 128 + ((c ^ (2 * (w & 3))) << 4));
      float O2[2][4][4];
      stage_dataA<false>(O2, BC, L);
#pragma unroll
      for (int v = 0; v < 4; v++)
        stg_relaxed4(&g_z1[((4 * v + j) * 8 + w) * 1024 + b * 8 + c], (pk<false>(O2[0][v][0], O2[0][v][1]) & ~1u) | tag,
                     pk<false>(O2[0][v][2], O2[0][v][3]), pk<false>(O2[1][v][0], O2[1][v][1]), pk<false>(O2[1][v][2], O2[1][v][3]));
      bar_sync(4, 288);
      if (tid == 0) red_add(&g_cnt[0], 1);
      TSTAMP(2);
    }
    {
      int laneB; asm volatile("mov.u32 %0, %1;" : "=r"(laneB) : "r"(lane) : "memory");
      const int c = laneB >> 2, j = laneB & 3, jj = c >> 1, part = c & 1;
      uint32_t AB[2][2][4], B8[2][2], B8i[2][2], BL[4][2][2];
      float M[2][2][2][6];
#pragma unroll
      for (int t = 0; t < 2; t++)
#pragma unroll
        for (int x = 0; x < 4; x++) aconst<false, 128>(-((c + 8 * (x & 1)) * (8 * (8 * t + 4 * (x >> 1) + j) + w)), 0.25f, 1.f, AB[0][t][x], AB[1][t][x]);
#pragma unroll
      for (int v = 0; v < 2; v++)
#pragma unroll
        for (int q = 0; q < 2; q++) {
          B8[v][q] = bconst<false, 8>(-((j + 4 * q) * (4 * v + jj)), 0.5f, part, 1.f);
          B8i[v][q] = bconst<INV_BF, 8>((j + 4 * q) * (4 * v + jj), 0.25f, part, 1.f);
        }
#pragma unroll
      for (int v = 0; v < 4; v++)
#pragma unroll
        for (int t = 0; t < 2; t++)
#pragma unroll
          for (int q = 0; q < 2; q++) BL[v][t][q] = bconst<INV_BF, 128>((8 * t + 4 * q + j) * (8 * (4 * v + jj) + w), 0.25f, part, 1.f);
#pragma unroll
      for (int tau = 0; tau < 2; tau++) {
        float ct, st;
        cexp<512>(16 * pgB + rmap(tau, c), ct, st);
        if (tau == 0 && special) ct = 0.f;
#pragma unroll
        for (int y = 0; y < 2; y++)
#pragma unroll
          for (int v = 0; v < 2; v++) {
            const float w1r = bf_lo(wraw[y][tau][v][0]) * 0.5f, w1i = bf_lo(wraw[y][tau][v][1]) * 0.5f;
            const float w2r = bf_lo(wraw[y][tau][v][2]) * 0.5f, w2i = -bf_lo(wraw[y][tau][v][3]) * 0.5f;
            const float pr = w1r + w2r, pi = w1i + w2i, qr = w1r - w2r, qi = w1i - w2i;
            float* m = M[y][tau][v];
            m[0] = pr - st * qr; m[1] = pi - st * qi; m[2] = pr + st * qr; m[3] = pi + st * qi; m[4] = ct * qr; m[5] = ct * qi;
            if (tau == 0 && special) { m[2] = bf_lo(wsp[y][v][0]); m[3] = bf_lo(wsp[y][v][1]); }
          }
      }
      TSTAMP(3);
      bar_sync(2, 288);
      TSTAMP(4);
      uint32_t in[4][4];
      load_tagged(in, &g_z1[b * 1024 + (8 * j + w) * 8 + c], 256, tag);
      TSTAMP(5);
      {
        float T[4][2][4];
        stage_dataB<false>(T, AB, in);
#pragma unroll
        for (int x = 0; x < 4; x++)
          sts4(E0 + w * 2080 + (c + 8 * (x >> 1)) * 128 + (((2 * j + (x & 1)) ^ (c & 1)) << 4), pk<false>(T[0][0][x], T[0][1][x]),
               pk<false>(T[1][0][x], T[1][1][x]), pk<false>(T[2][0][x], T[2][1][x]), pk<false>(T[3][0][x], T[3][1][x]));
      }
      bar_sync(1, 256);
#pragma unroll
      for (int y = 0; y < 2; y++) {
        uint32_t L0[4], L1[4];
        lds4(L0, E0 + j * 2080 + (2 * w + y) * 128 + ((c ^ y) << 4));
        lds4(L1, E0 + (j + 4) * 2080 + (2 * w + y) * 128 + ((c ^ y) << 4));
        float G[2][2][4];
#pragma unroll
        for (int tau = 0; tau < 2; tau++) {
          uint32_t a[4];
#pragma unroll
          for (int v = 0; v < 2; v++) {
            float Y[4] = {0.f, 0.f, 0.f, 0.f};
            mma16816<false>(Y, L0[2 * tau], L0[2 * tau + 1], L1[2 * tau], L1[2 * tau + 1], B8[v][0], B8[v][1]);
            const float* m = M[y][tau][v];
            const float ur = m[0] * Y[0] - m[1] * Y[1] - m[4] * Y[3] - m[5] * Y[2];
            const float ui = m[0] * Y[1] + m[1] * Y[0] + m[4] * Y[2] - m[5] * Y[3];
            const float vr = m[2] * Y[2] - m[3] * Y[3] + m[4] * Y[1] + m[5] * Y[0];
            const float vi = m[2] * Y[3] + m[3] * Y[2] - m[4] * Y[0] + m[5] * Y[1];
            a[2 * v] = pk<INV_BF>(ur, ui); a[2 * v + 1] = pk<INV_BF>(vr, vi);
          }
#pragma unroll
          for (int v = 0; v < 2; v++) {
#pragma unroll
            for (int x = 0; x < 4; x++) G[tau][v][x] = 0.f;
            mma16816<INV_BF>(G[tau][v], a[0], a[1], a[2], a[3], B8i[v][0], B8i[v][1]);
          }
        }
#pragma unroll
        for (int v = 0; v < 2; v++)
          sts4(E1 + (4 * v + j) * 2080 + (2 * w + y) * 128 + ((c ^ (2 * ((2 * w + y) & 3))) << 4), pk<INV_BF>(G[0][v][0], G[0][v][1]),
               pk<INV_BF>(G[0][v][2], G[0][v][3]), pk<INV_BF>(G[1][v][0], G[1][v][1]), pk<INV_BF>(G[1][v][2], G[1][v][3]));
      }
      bar_sync(1, 256);
      uint32_t L[4][4];
#pragma unroll
      for (int q = 0; q < 4; q++) lds4(L[q], E1 + w * 2080 + (j + 4 * q) * 128 + ((c ^ (2 * j)) << 4));
      float O2[2][4][4];
      stage_dataA<INV_BF>(O2, BL, L);
#pragma unroll
      for (int v = 0; v < 4; v++)
        stg_relaxed4(&g_z2[(8 * (4 * v + j) + w) * 1024 + b * 8 + c], (pk<INV_BF>(O2[0][v][0], O2[0][v][1]) & ~1u) | tag,
                     pk<INV_BF>(O2[0][v][2], O2[0][v][3]), pk<INV_BF>(O2[1][v][0], O2[1][v][1]), pk<INV_BF>(O2[1][v][2], O2[1][v][3]));
      bar_sync(1, 256);
      if (tid == 0) red_add(&g_cnt[32], 1);
      TSTAMP(6);
    }
    {
      int laneC; asm volatile("mov.u32 %0, %1;" : "=r"(laneC) : "r"(lane) : "memory");
      const int c = laneC >> 2, j = laneC & 3, jj = c >> 1, part = c & 1;
      uint32_t AC[2][2][4], A1[2][2][4], B2[4][2][2];
      float tw[2][4][2];
#pragma unroll
      for (int t = 0; t < 2; t++)
#pragma unroll
        for (int x = 0; x < 4; x++) {
          aconst<INV_BF, 2048>((8 * t + 4 * (x >> 1) + j) * (128 * (c + 8 * (x & 1)) + b), 0.25f, 1.f, AC[0][t][x], AC[1][t][x]);
          aconst<INV_BF, 16>((2 * c + (x & 1)) * k2map(2 * t + (x >> 1), j), 0.25f, (x >> 1) ? -1.f : 1.f, A1[0][t][x], A1[1][t][x]);
        }
#pragma unroll
      for (int uu = 0; uu < 2; uu++)
#pragma unroll
        for (int x = 0; x < 4; x++) cexp<256>((2 * c + (x >> 1)) * rmap(uu, 2 * j + (x & 1)), tw[uu][x][0], tw[uu][x][1]);
#pragma unroll
      for (int v = 0; v < 4; v++)
#pragma unroll
        for (int uu = 0; uu < 2; uu++)
#pragma unroll
          for (int q = 0; q < 2; q++) B2[v][uu][q] = bconst<INV_BF, 16>((4 * v + jj) * rmap(uu, 2 * j + q), 0.25f, part, 1.f);
      bar_sync(2, 288);
      TSTAMP(7);
      uint32_t in[4][4];
      load_tagged(in, &g_z2[b * 1024 + (8 * j + w) * 8 + c], 256, tag);
      TSTAMP(8);
      {
        float T[4][2][4];
        stage_dataB<INV_BF>(T, AC, in);
#pragma unroll
        for (int x = 0; x < 4; x++)
          sts4(E0 + (c + 8 * (x >> 1)) * 1040 + w * 128 + (((2 * j + (x & 1)) ^ (2 * (w & 3))) << 4), pk<INV_BF>(T[0][0][x], T[0][1][x]),
               pk<INV_BF>(T[1][0][x], T[1][1][x]), pk<INV_BF>(T[2][0][x], T[2][1][x]), pk<INV_BF>(T[3][0][x], T[3][1][x]));
      }
      bar_sync(1, 256);
      float hv[2][16], s1[2], s2[2];
#pragma unroll
      for (int u = 0; u < 2; u++) {
        uint32_t P[2][4], z[4][2], tv[2];
#pragma unroll
        for (int g = 0; g < 2; g++) {
          lds4(P[g], E0 + (2 * w + u) * 1040 + (j + 4 * g) * 128 + ((c ^ (2 * j)) << 4));
          tv[g] = __shfl_sync(~0u, P[g][1], (lane & ~3) | ((lane + 1) & 3));
        }
#pragma unroll
        for (int g = 0; g < 2; g++) {
          z[2 * g][0] = P[g][0]; z[2 * g][1] = P[g][2];
          z[2 * g + 1][1] = c ? P[g][1] : P[g][3];
          z[2 * g + 1][0] = c ? P[g][3] : (j < 3 ? tv[g] : tv[g ^ 1]);
        }
        float O[4][4];
        fft256<INV_BF>(O, z, A1, tw, B2);
        s1[u] = 0.f;
#pragma unroll
        for (int v = 0; v < 4; v++) {
          const uint32_t y0 = pk<true>(O[v][0], O[v][1]), y1 = pk<true>(O[v][2], O[v][3]);
          const uint32_t h0 = pk<true>(bf_lo(xr[u][v].x) + bf_lo(y0), bf_hi(xr[u][v].x) + bf_hi(y0));
          const uint32_t h1 = pk<true>(bf_lo(xr[u][v].y) + bf_lo(y1), bf_hi(xr[u][v].y) + bf_hi(y1));
          xr[u][v].x = h0; xr[u][v].y = h1;
          hv[u][4 * v] = bf_lo(h0); hv[u][4 * v + 1] = bf_hi(h0); hv[u][4 * v + 2] = bf_lo(h1); hv[u][4 * v + 3] = bf_hi(h1);
          s1[u] += (hv[u][4 * v] + hv[u][4 * v + 1]) + (hv[u][4 * v + 2] + hv[u][4 * v + 3]);
        }
      }
#pragma unroll
      for (int o = 16; o > 0; o >>= 1) { s1[0] += __shfl_xor_sync(~0u, s1[0], o); s1[1] += __shfl_xor_sync(~0u, s1[1], o); }
#pragma unroll
      for (int u = 0; u < 2; u++) {
        const float mean = s1[u] * (1.f / D_);
        s2[u] = 0.f;
#pragma unroll
        for (int i = 0; i < 16; i++) { const float t = hv[u][i] - mean; s2[u] = fmaf(t, t, s2[u]); }
      }
#pragma unroll
      for (int o = 16; o > 0; o >>= 1) { s2[0] += __shfl_xor_sync(~0u, s2[0], o); s2[1] += __shfl_xor_sync(~0u, s2[1], o); }
#pragma unroll
      for (int u = 0; u < 2; u++) {
        const float mb = bf_round(s1[u] * (1.f / D_));
        const float den = bf_round(sqrtf(bf_round(bf_round(s2[u] * (1.f / D_)) + 1e-5f)));
        const float inv = 1.f / den;
        __nv_bfloat16* dst = g_ln2 + (size_t)(b * 16 + 2 * w + u) * D_ + 32 * j + 4 * c;
#pragma unroll
        for (int v = 0; v < 4; v++) {
          const uint32_t d0 = pk<true>(hv[u][4 * v] - mb, hv[u][4 * v + 1] - mb), d1 = pk<true>(hv[u][4 * v + 2] - mb, hv[u][4 * v + 3] - mb);
          uint2 o;
          o.x = pk<true>(bf_lo(d0) * inv, bf_hi(d0) * inv); o.y = pk<true>(bf_lo(d1) * inv, bf_hi(d1) * inv);
          *reinterpret_cast<uint2*>(dst + 128 * v) = o;
        }
      }
      bar_arrive(3, 288);
      TSTAMP(9);
    }
    asm volatile("barrier.cluster.wait.acquire.aligned;" ::: "memory");
    const int wg = warp >> 2, t128 = tid & 127;
    const uint64_t descA0 = mkdesc(sb + SM_A + wg * 8192, 16, 1024, 1);
    const uint64_t descB1 = mkdesc(sb + SM_RING, 2048, 512, 2);
    const uint64_t descB2 = mkdesc(sb + SM_RING, 16, 1024, 1);
    uint32_t act[28][4];
    int slot = 0; uint32_t ph = 0;
    mbar_wait(bar + 8 * B_AFULL, 0);
    TSTAMP(10);
#pragma unroll
    for (int u = 0; u < 2; u++)
#pragma unroll
      for (int v = 0; v < 4; v++)
        *reinterpret_cast<uint2*>(g_h + (size_t)(b * 16 + 2 * w + u) * D_ + 32 * j + 4 * c + 128 * v) = xr[u][v];
    bar_arrive(10, 288);
    {
      float acc[128];
#pragma unroll 1
      for (int st = 0; st < 16; st++) {
        if ((st & 1) == 0) mbar_wait(bar + 8 * (B_AFULL + (st >> 1)), 0);
        mbar_wait(bar + 8 * (B_FULL + slot), ph);
        const uint64_t da = descA0 + (uint64_t)(((st >> 1) * 16384 + (st & 1) * 64) >> 4), db = descB1 + (uint64_t)((slot * SLOT_BYTES) >> 4);
        wg_fence();
        wgmma_ss_n256(acc, da, db, st);
        wgmma_ss_n256(acc, da + 2, db + 64, 1);
        wg_commit();
        if (st > 0) { wg_wait<1>(); if (lane == 0) mbar_arrive(bar + 8 * (B_EMPTY + (slot == 0 ? NSLOT - 1 : slot - 1))); }
        if (++slot == NSLOT) { slot = 0; ph ^= 1; }
      }
      wg_wait<0>();
      reg_fence(acc);
      if (lane == 0) mbar_arrive(bar + 8 * (B_EMPTY + (slot == 0 ? NSLOT - 1 : slot - 1)));
      TSTAMP(11);
#pragma unroll
      for (int kk = 0; kk < 8; kk++)
#pragma unroll
        for (int x = 0; x < 4; x++)
          act[kk][x] = pk<true>(silu_mul(acc[8 * kk + 2 * x], acc[64 + 8 * kk + 2 * x]), silu_mul(acc[8 * kk + 2 * x + 1], acc[64 + 8 * kk + 2 * x + 1]));
    }
    const uint32_t peerA = mapa(sb + SM_A + wg * 8192 + t128 * 16, e_ ^ 1);
    const uint32_t peerBar = mapa(bar, e_ ^ 1);
    {
      float acc[96];
#pragma unroll 1
      for (int st = 0; st < 16; st++) {
        mbar_wait(bar + 8 * (B_FULL + slot), ph);
        const uint64_t da = descA0 + (uint64_t)(((st >> 1) * 16384 + (st & 1) * 64) >> 4), db = descB1 + (uint64_t)((slot * SLOT_BYTES) >> 4);
        wg_fence();
        wgmma_ss_n192(acc, da, db, st);
        wgmma_ss_n192(acc, da + 2, db + 64, 1);
        wg_commit();
        if (st > 0) { wg_wait<1>(); if (lane == 0) mbar_arrive(bar + 8 * (B_EMPTY + (slot == 0 ? NSLOT - 1 : slot - 1))); }
        if (st == 8 && lane == 0) mbar_arrive_remote(peerBar + 8 * (B_PFREE + wg));
        if (st == 11) {
          mbar_wait_cluster(bar + 8 * (B_PFREE + wg), 0);
#pragma unroll
          for (int kk = 0; kk < 8; kk++)
            asm volatile("st.async.weak.shared::cluster.mbarrier::complete_tx::bytes.v4.b32 [%0], {%1,%2,%3,%4}, [%5];"
                         ::"r"(peerA + (kk >> 2) * 16384 + (kk & 3) * 2048), "r"(act[kk][0]), "r"(act[kk][1]), "r"(act[kk][2]), "r"(act[kk][3]),
                           "r"(peerBar + 8 * (B_ACT + 2 * wg)) : "memory");
        }
        if (++slot == NSLOT) { slot = 0; ph ^= 1; }
      }
      wg_wait<0>();
      reg_fence(acc);
      if (lane == 0) mbar_arrive(bar + 8 * (B_EMPTY + (slot == 0 ? NSLOT - 1 : slot - 1)));
      bar_arrive(5, 288);
      TSTAMP(12);
#pragma unroll
      for (int kk = 0; kk < 6; kk++) {
#pragma unroll
        for (int x = 0; x < 4; x++)
          act[8 + kk][x] = pk<true>(silu_mul(acc[8 * kk + 2 * x], acc[48 + 8 * kk + 2 * x]), silu_mul(acc[8 * kk + 2 * x + 1], acc[48 + 8 * kk + 2 * x + 1]));
        asm volatile("st.async.weak.shared::cluster.mbarrier::complete_tx::bytes.v4.b32 [%0], {%1,%2,%3,%4}, [%5];"
                     ::"r"(peerA + (2 + (kk >> 2)) * 16384 + (kk & 3) * 2048), "r"(act[8 + kk][0]), "r"(act[8 + kk][1]), "r"(act[8 + kk][2]), "r"(act[8 + kk][3]),
                       "r"(peerBar + 8 * (B_ACT + 2 * wg + 1)) : "memory");
      }
    }
    {
      float acc[2][32];
      const uint32_t myA = sb + SM_A + wg * 8192 + t128 * 16;
#pragma unroll
      for (int t = 0; t < 4; t++) {
#pragma unroll
        for (int qq = 0; qq < 4; qq++) {
          if (t == 0 && qq == 1) {
            mbar_wait_cluster(bar + 8 * (B_ACT + 2 * wg), 0);
#pragma unroll
            for (int kk = 0; kk < 8; kk++) lds4(act[14 + kk], myA + (kk >> 2) * 16384 + (kk & 3) * 2048);
          }
          if (t == 0 && qq == 3) {
            mbar_wait_cluster(bar + 8 * (B_ACT + 2 * wg + 1), 0);
#pragma unroll
            for (int kk = 0; kk < 6; kk++) lds4(act[22 + kk], myA + (2 + (kk >> 2)) * 16384 + (kk & 3) * 2048);
          }
          mbar_wait(bar + 8 * (B_FULL + slot), ph);
          const uint64_t db = descB2 + (uint64_t)((slot * SLOT_BYTES) >> 4);
          wg_fence();
#pragma unroll
          for (int kk = 0; kk < 7; kk++)
            wgmma_rs_n64(acc[t & 1], act[qq * 7 + kk][0], act[qq * 7 + kk][1], act[qq * 7 + kk][2], act[qq * 7 + kk][3], db + kk * 128, (qq | kk) != 0);
          wg_commit();
          if (t > 0 || qq > 0) { wg_wait<1>(); if (lane == 0) mbar_arrive(bar + 8 * (B_EMPTY + (slot == 0 ? NSLOT - 1 : slot - 1))); }
          if (t > 0 && qq == 0) {
            float (&pa)[32] = acc[(t - 1) & 1];
            reg_fence(pa);
            const int q = (r4 + t) & 3;
            uint4* dst = &g_part[((mblk * 8 + q * 2 + e_) * 3 + (t - 1)) * 1024 + wg * 512 + t128];
#pragma unroll
            for (int i = 0; i < 4; i++)
              dst[i * 128] = make_uint4(pk<true>(pa[8 * i], pa[8 * i + 1]), pk<true>(pa[8 * i + 2], pa[8 * i + 3]),
                                        pk<true>(pa[8 * i + 4], pa[8 * i + 5]), pk<true>(pa[8 * i + 6], pa[8 * i + 7]));
            __syncwarp();
            if (lane == 0) mbar_arrive(bar + 8 * (B_PST + (t - 1) * 2 + wg));
          }
          if (++slot == NSLOT) { slot = 0; ph ^= 1; }
        }
      }
      wg_wait<0>();
      float (&fa)[32] = acc[1];
      reg_fence(fa);
      TSTAMP(13);
      mbar_wait(bar + 8 * (B_PART + wg), 0);
      TSTAMP(14);
#pragma unroll
      for (int t = 0; t < 3; t++)
#pragma unroll
        for (int i = 0; i < 4; i++) {
          uint32_t pv[4];
          lds4(pv, sb + SM_A + (4 + t) * 16384 + wg * 8192 + i * 2048 + t128 * 16);
#pragma unroll
          for (int x = 0; x < 4; x++) { fa[8 * i + 2 * x] += bf_lo(pv[x]); fa[8 * i + 2 * x + 1] += bf_hi(pv[x]); }
        }
      const uint32_t ht = sb + SM_A + 7 * 16384 + wg * 8192;
      const int mrow = (warp & 3) * 16 + (lane & 7) + ((lane >> 3) & 1) * 8;
#pragma unroll
      for (int i = 0; i < 4; i++) {
        const uint32_t ad = ht + mrow * 128 + (((2 * i + (lane >> 4)) ^ (lane & 7)) << 4);
        uint32_t hq[4];
        asm volatile("ldmatrix.sync.aligned.m8n8.x4.shared.b16 {%0,%1,%2,%3}, [%4];" : "=r"(hq[0]), "=r"(hq[1]), "=r"(hq[2]), "=r"(hq[3]) : "r"(ad) : "memory");
#pragma unroll
        for (int x = 0; x < 4; x++) {
          const uint32_t dv = pk<true>(fa[8 * i + 2 * x], fa[8 * i + 2 * x + 1]);
          hq[x] = pk<true>(bf_lo(hq[x]) + bf_lo(dv), bf_hi(hq[x]) + bf_hi(dv));
        }
        asm volatile("stmatrix.sync.aligned.m8n8.x4.shared.b16 [%0], {%1,%2,%3,%4};" ::"r"(ad), "r"(hq[0]), "r"(hq[1]), "r"(hq[2]), "r"(hq[3]) : "memory");
      }
      asm volatile("fence.proxy.async.shared::cta;" ::: "memory");
      bar_sync(8 + wg, 128);
      if (t128 == 0) {
        asm volatile("cp.async.bulk.tensor.3d.global.shared::cta.bulk_group [%0, {%2, %3, %4}], [%1];"
                     ::"l"(&maps.o), "r"(ht), "r"(e_ * 256 + r4 * 64), "r"(0), "r"(mblk * 8 + wg * 4) : "memory");
        asm volatile("cp.async.bulk.commit_group;" ::: "memory");
        asm volatile("cp.async.bulk.wait_group.read 0;" ::: "memory");
      }
      TSTAMP(15);
    }
  }
}

typedef CUresult (*EncFn)(CUtensorMap*, CUtensorMapDataType, cuuint32_t, void*, const cuuint64_t*, const cuuint64_t*, const cuuint32_t*,
                          const cuuint32_t*, CUtensorMapInterleave, CUtensorMapSwizzle, CUtensorMapL2promotion, CUtensorMapFloatOOBfill);

void enc(EncFn f, CUtensorMap* m, int rank, const void* base, const cuuint64_t* dims, const cuuint64_t* strides, const cuuint32_t* box, CUtensorMapSwizzle sw) {
  cuuint32_t es[3] = {1, 1, 1};
  f(m, CU_TENSOR_MAP_DATA_TYPE_BFLOAT16, rank, const_cast<void*>(base), dims, strides, box, es, CU_TENSOR_MAP_INTERLEAVE_NONE, sw,
    CU_TENSOR_MAP_L2_PROMOTION_L2_128B, CU_TENSOR_MAP_FLOAT_OOB_FILL_NONE);
}

}

extern "C" void kernel_launch(void* const* d_in, const int* in_sizes, int n_in, void* d_out, int out_size) {
  (void)in_sizes; (void)n_in; (void)out_size;
  static EncFn f = nullptr;
  static void *p_ln2 = nullptr, *p_h = nullptr;
  if (!f) {
    void* fn = nullptr; cudaDriverEntryPointQueryResult qr;
    cudaGetDriverEntryPoint("cuTensorMapEncodeTiled", &fn, cudaEnableDefault, &qr);
    f = (EncFn)fn;
    cudaFuncSetAttribute(fused_kernel, cudaFuncAttributeMaxDynamicSharedMemorySize, SMEM_BYTES);
    cudaGetSymbolAddress(&p_ln2, g_ln2);
    cudaGetSymbolAddress(&p_h, g_h);
  }
  Maps maps;
  {
    cuuint64_t d3[3] = {32, 512, 56}, s3[2] = {F_ * 2, 64};
    cuuint32_t b4[3] = {32, 32, 4}, b3[3] = {32, 32, 3};
    enc(f, &maps.g4, 3, d_in[4], d3, s3, b4, CU_TENSOR_MAP_SWIZZLE_64B);
    enc(f, &maps.u4, 3, d_in[5], d3, s3, b4, CU_TENSOR_MAP_SWIZZLE_64B);
    enc(f, &maps.g3, 3, d_in[4], d3, s3, b3, CU_TENSOR_MAP_SWIZZLE_64B);
    enc(f, &maps.u3, 3, d_in[5], d3, s3, b3, CU_TENSOR_MAP_SWIZZLE_64B);
    cuuint64_t dd[2] = {D_, F_}, sd[1] = {D_ * 2};
    cuuint32_t bd[2] = {64, 112};
    enc(f, &maps.dn, 2, d_in[6], dd, sd, bd, CU_TENSOR_MAP_SWIZZLE_128B);
    cuuint64_t da[2] = {D_, S_};
    cuuint32_t ba[2] = {64, 128}, bh[2] = {64, 64};
    enc(f, &maps.a, 2, p_ln2, da, sd, ba, CU_TENSOR_MAP_SWIZZLE_128B);
    enc(f, &maps.h, 2, p_h, da, sd, bh, CU_TENSOR_MAP_SWIZZLE_128B);
    cuuint64_t dO[3] = {D_, 16, 128}, sO[2] = {128 * D_ * 2, D_ * 2};
    cuuint32_t bO[3] = {64, 16, 4};
    enc(f, &maps.o, 3, d_out, dO, sO, bO, CU_TENSOR_MAP_SWIZZLE_128B);
  }
  fused_kernel<<<NCTA, 384, SMEM_BYTES>>>(maps, (const __nv_bfloat16*)d_in[0], (const unsigned short*)d_in[1], (const unsigned short*)d_in[2],
                                          (const char*)d_in[4], (const char*)d_in[5], (const char*)d_in[6]);
}
```

```cpp
#include <cuda_runtime.h>
#include <cuda.h>
#include <cuda_bf16.h>
#include <cuda_fp16.h>
#include <stdint.h>


namespace {

constexpr int S_ = 2048, D_ = 512, F_ = 1792, WCOLS = 257;
constexpr int NCTA = 128;
constexpr int NGRP = 4, NREP = 8;
constexpr int SV = 2;
constexpr int NSLOT = 6, SLOT_BYTES = 16384;
constexpr int SM_A = 0;
constexpr int SM_RING = 131072;
constexpr int SM_BAR = SM_RING + NSLOT * SLOT_BYTES;
constexpr int SM_TOTAL = SM_BAR + 1024;
constexpr int SMEM_BYTES = SM_TOTAL + 1024;
constexpr int SM_CA = 63488 - 6144, SM_CC = SM_CA + 6144, SM_C8 = SM_CA + 12288, SM_CB = SM_CA + 13312, SM_BC = SM_CA + 46080, SM_AC = SM_BC + 2048;
constexpr int SM_X = 114688;
constexpr int SM_W = SM_RING + 49152;
constexpr int B_FULL = 0, B_EMPTY = 6, B_AFULL = 12, B_PFREE = 20, B_ACT = 24, B_PART = 30, B_X = 32, B_T = 34, B_LN = 35, B_L0 = 36, B_RS = 38, B_NUM = 39;
constexpr uint32_t G2_T = 0xFFAA5044u, G2_Q = 0xE4E4EE50u;

struct Scratch {
  unsigned epoch, pad0[31];
  unsigned cnt[2 * 256 * 32];
  unsigned cntC[16 * 32];
  unsigned flagH[NCTA];
  unsigned pad1[352];
  float rstd[S_];
  uint4 z1[NCTA * 1024];
  uint4 z2[NCTA * 1024];
  __nv_bfloat16 ln2[S_ * D_];
  __nv_bfloat16 h[S_ * D_];
  uint4 part[NCTA * 3 * 1024];
};
__device__ __align__(1024) Scratch g_s;

__device__ __align__(128) const uint32_t g_table[11520] = {
0x3e80,0x3e80,0x3e80,0x3e80,0x3e80,0xbe80,0x3e80,0xbe80,0x3e80,0x3e80,0x3e80,0x3e80,
0x3e80,0xbe80,0x3e80,0xbe80,0x3e80,0x3e80,0x3e800000,0xbe800000,0x3dc43e6d,0xbdc43e6d,0x3e6dbdc4,0xbe6dbdc4,
0x3e353e35,0xbe353e35,0x3e35be35,0xbe35be35,0x3e6d3dc4,0xbe6d3dc4,0x3dc4be6d,0xbdc4be6d,0x3e80,0x3e80,0xbe80,0xbe80,
0x3e353e35,0xbe353e35,0xbe35be35,0x3e35be35,0x3e800000,0xbe800000,0xbe800000,0x3e800000,0x3e35be35,0xbe35be35,0xbe353e35,0x3e353e35,
0x3e80,0x3e80,0xbe800000,0x3e800000,0x3e6d3dc4,0xbe6d3dc4,0xbdc43e6d,0x3dc43e6d,0x3e35be35,0xbe35be35,0x3e353e35,0xbe353e35,
0xbdc4be6d,0x3dc4be6d,0x3e6dbdc4,0xbe6dbdc4,0x3e80,0x3e80,0x3e80,0x3e80,0x3e800000,0xbe800000,0x3e800000,0xbe800000,
0xbe80,0xbe80,0xbe80,0xbe80,0xbe800000,0x3e800000,0xbe800000,0x3e800000,0x3e80,0x3e80,0x3e800000,0xbe800000,
0x3e6dbdc4,0xbe6dbdc4,0xbdc4be6d,0x3dc4be6d,0xbe35be35,0x3e35be35,0xbe353e35,0x3e353e35,0xbdc43e6d,0x3dc43e6d,0x3e6d3dc4,0xbe6d3dc4,
0x3e80,0x3e80,0xbe80,0xbe80,0x3e35be35,0xbe35be35,0xbe353e35,0x3e353e35,0xbe800000,0x3e800000,0x3e800000,0xbe800000,
0x3e353e35,0xbe353e35,0xbe35be35,0x3e35be35,0x3e80,0x3e80,0xbe800000,0x3e800000,0x3dc4be6d,0xbdc4be6d,0x3e6d3dc4,0xbe6d3dc4,
0xbe353e35,0x3e353e35,0xbe35be35,0x3e35be35,0x3e6dbdc4,0xbe6dbdc4,0x3dc43e6d,0xbdc43e6d,0x3e80,0x3e80,0x3e80,0x3e80,
0x3e80,0xbe80,0x3e80,0xbe80,0x3e80,0x3e80,0x3e80,0x3e80,0x3e80,0xbe80,0x3e80,0xbe80,
0xbe80,0xbe80,0xbe800000,0x3e800000,0xbdc4be6d,0x3dc4be6d,0xbe6d3dc4,0x3e6d3dc4,0xbe35be35,0x3e35be35,0xbe353e35,0x3e353e35,
0xbe6dbdc4,0x3e6dbdc4,0xbdc43e6d,0x3dc43e6d,0x3e80,0x3e80,0xbe80,0xbe80,0x3e353e35,0xbe353e35,0xbe35be35,0x3e35be35,
0x3e800000,0xbe800000,0xbe800000,0x3e800000,0x3e35be35,0xbe35be35,0xbe353e35,0x3e353e35,0xbe80,0xbe80,0x3e800000,0xbe800000,
0xbe6dbdc4,0x3e6dbdc4,0x3dc4be6d,0xbdc4be6d,0xbe353e35,0x3e353e35,0xbe35be35,0x3e35be35,0x3dc43e6d,0xbdc43e6d,0xbe6d3dc4,0x3e6d3dc4,
0x3e80,0x3e80,0x3e80,0x3e80,0x3e800000,0xbe800000,0x3e800000,0xbe800000,0xbe80,0xbe80,0xbe80,0xbe80,
0xbe800000,0x3e800000,0xbe800000,0x3e800000,0xbe80,0xbe80,0xbe800000,0x3e800000,0xbe6d3dc4,0x3e6d3dc4,0x3dc43e6d,0xbdc43e6d,
0x3e353e35,0xbe353e35,0x3e35be35,0xbe35be35,0x3dc4be6d,0xbdc4be6d,0xbe6dbdc4,0x3e6dbdc4,0x3e80,0x3e80,0xbe80,0xbe80,
0x3e35be35,0xbe35be35,0xbe353e35,0x3e353e35,0xbe800000,0x3e800000,0x3e800000,0xbe800000,0x3e353e35,0xbe353e35,0xbe35be35,0x3e35be35,
0xbe80,0xbe80,0x3e800000,0xbe800000,0xbdc43e6d,0x3dc43e6d,0xbe6dbdc4,0x3e6dbdc4,0x3e35be35,0xbe35be35,0x3e353e35,0xbe353e35,
0xbe6d3dc4,0x3e6d3dc4,0xbdc4be6d,0x3dc4be6d,0x3e800000,0x3e800000,0x3e800000,0x3e800000,0x3e800000,0xbe800000,0x3e800000,0xbe800000,
0x3e800000,0x3e800000,0x3e800000,0x3e800000,0x3e800000,0xbe800000,0x3e800000,0xbe800000,0x3e800000,0x3e800000,0xbe80,0x3e80,
0x3e6dbdc4,0x3e6d3dc4,0xbdc4be6d,0xbdc43e6d,0x3e35be35,0x3e353e35,0xbe35be35,0xbe353e35,0x3dc4be6d,0x3dc43e6d,0xbe6dbdc4,0xbe6d3dc4,
0x3e800000,0x3e800000,0xbe800000,0xbe800000,0x3e35be35,0x3e353e35,0xbe353e35,0xbe35be35,0xbe80,0x3e80,0x3e80,0xbe80,
0xbe35be35,0xbe353e35,0x3e353e35,0x3e35be35,0x3e800000,0x3e800000,0x3e80,0xbe80,0x3dc4be6d,0x3dc43e6d,0x3e6d3dc4,0x3e6dbdc4,
0xbe35be35,0xbe353e35,0x3e35be35,0x3e353e35,0xbe6d3dc4,0xbe6dbdc4,0xbdc4be6d,0xbdc43e6d,0x3e800000,0x3e800000,0x3e800000,0x3e800000,
0xbe80,0x3e80,0xbe80,0x3e80,0xbe800000,0xbe800000,0xbe800000,0xbe800000,0x3e80,0xbe80,0x3e80,0xbe80,
0x3e800000,0x3e800000,0xbe80,0x3e80,0xbdc4be6d,0xbdc43e6d,0xbe6d3dc4,0xbe6dbdc4,0xbe353e35,0xbe35be35,0x3e353e35,0x3e35be35,
0x3e6d3dc4,0x3e6dbdc4,0x3dc4be6d,0x3dc43e6d,0x3e800000,0x3e800000,0xbe800000,0xbe800000,0xbe35be35,0xbe353e35,0x3e353e35,0x3e35be35,
0x3e80,0xbe80,0xbe80,0x3e80,0x3e35be35,0x3e353e35,0xbe353e35,0xbe35be35,0x3e800000,0x3e800000,0x3e80,0xbe80,
0xbe6dbdc4,0xbe6d3dc4,0x3dc4be6d,0x3dc43e6d,0x3e353e35,0x3e35be35,0xbe353e35,0xbe35be35,0xbdc4be6d,0xbdc43e6d,0x3e6dbdc4,0x3e6d3dc4,
0x3e800000,0x3e800000,0x3e800000,0x3e800000,0x3e800000,0xbe800000,0x3e800000,0xbe800000,0x3e800000,0x3e800000,0x3e800000,0x3e800000,
0x3e800000,0xbe800000,0x3e800000,0xbe800000,0xbe800000,0xbe800000,0x3e80,0xbe80,0xbe6d3dc4,0xbe6dbdc4,0x3dc43e6d,0x3dc4be6d,
0xbe353e35,0xbe35be35,0x3e353e35,0x3e35be35,0xbdc43e6d,0xbdc4be6d,0x3e6d3dc4,0x3e6dbdc4,0x3e800000,0x3e800000,0xbe800000,0xbe800000,
0x3e35be35,0x3e353e35,0xbe353e35,0xbe35be35,0xbe80,0x3e80,0x3e80,0xbe80,0xbe35be35,0xbe353e35,0x3e353e35,0x3e35be35,
0xbe800000,0xbe800000,0xbe80,0x3e80,0xbdc43e6d,0xbdc4be6d,0xbe6dbdc4,0xbe6d3dc4,0x3e353e35,0x3e35be35,0xbe353e35,0xbe35be35,
0x3e6dbdc4,0x3e6d3dc4,0x3dc43e6d,0x3dc4be6d,0x3e800000,0x3e800000,0x3e800000,0x3e800000,0xbe80,0x3e80,0xbe80,0x3e80,
0xbe800000,0xbe800000,0xbe800000,0xbe800000,0x3e80,0xbe80,0x3e80,0xbe80,0xbe800000,0xbe800000,0x3e80,0xbe80,
0x3dc43e6d,0x3dc4be6d,0x3e6dbdc4,0x3e6d3dc4,0x3e35be35,0x3e353e35,0xbe35be35,0xbe353e35,0xbe6dbdc4,0xbe6d3dc4,0xbdc43e6d,0xbdc4be6d,
0x3e800000,0x3e800000,0xbe800000,0xbe800000,0xbe35be35,0xbe353e35,0x3e353e35,0x3e35be35,0x3e80,0xbe80,0xbe80,0x3e80,
0x3e35be35,0x3e353e35,0xbe353e35,0xbe35be35,0xbe800000,0xbe800000,0xbe80,0x3e80,0x3e6d3dc4,0x3e6dbdc4,0xbdc43e6d,0xbdc4be6d,
0xbe35be35,0xbe353e35,0x3e35be35,0x3e353e35,0x3dc43e6d,0x3dc4be6d,0xbe6d3dc4,0xbe6dbdc4,0x3f800000,0x80000000,0x3f800000,0x80000000,
0x3f800000,0x80000000,0x3f800000,0x80000000,0x3f800000,0x80000000,0x3f800000,0x80000000,0x3f800000,0x80000000,0x3f800000,0x80000000,
0x3f800000,0x80000000,0x3f7fb10f,0xbd48fb30,0x3f7ec46d,0xbdc8bd36,0x3f7d3aac,0xbe164083,0x3f7b14be,0xbe47c5c2,0x3f7853f8,0xbe78cfcc,
0x3f74fa0b,0xbe94a031,0x3f710908,0xbeac7cd4,0x3f800000,0x80000000,0x3f7ec46d,0xbdc8bd36,0x3f7b14be,0xbe47c5c2,0x3f74fa0b,0xbe94a031,
0x3f6c835e,0xbec3ef15,0x3f61c598,0xbef15aea,0x3f54db31,0xbf0e39da,0x3f45e403,0xbf226799,0x3f800000,0x80000000,0x3f7d3aac,0xbe164083,
0x3f74fa0b,0xbe94a031,0x3f676bd8,0xbedae880,0x3f54db31,0xbf0e39da,0x3f3daef9,0xbf2beb4a,0x3f226799,0xbf45e403,0x3f039c3d,0xbf5b941a,
0x3f800000,0x80000000,0x3f7b14be,0xbe47c5c2,0x3f6c835e,0xbec3ef15,0x3f54db31,0xbf0e39da,0x3f3504f3,0xbf3504f3,0x3f0e39da,0xbf54db31,
0x3ec3ef15,0xbf6c835e,0x3e47c5c2,0xbf7b14be,0x3f800000,0x80000000,0x3f7853f8,0xbe78cfcc,0x3f61c598,0xbef15aea,0x3f3daef9,0xbf2beb4a,
0x3f0e39da,0xbf54db31,0x3eac7cd4,0xbf710908,0x3dc8bd36,0xbf7ec46d,0xbe164083,0xbf7d3aac,0x3f800000,0x80000000,0x3f74fa0b,0xbe94a031,
0x3f54db31,0xbf0e39da,0x3f226799,0xbf45e403,0x3ec3ef15,0xbf6c835e,0x3dc8bd36,0xbf7ec46d,0xbe47c5c2,0xbf7b14be,0xbef15aea,0xbf61c598,
0x3f800000,0x80000000,0x3f710908,0xbeac7cd4,0x3f45e403,0xbf226799,0x3f039c3d,0xbf5b941a,0x3e47c5c2,0xbf7b14be,0xbe164083,0xbf7d3aac,
0xbef15aea,0xbf61c598,0xbf3daef9,0xbf2beb4a,0x3f800000,0x80000000,0x3f6c835e,0xbec3ef15,0x3f3504f3,0xbf3504f3,0x3ec3ef15,0xbf6c835e,
0x248d3132,0xbf800000,0xbec3ef15,0xbf6c835e,0xbf3504f3,0xbf3504f3,0xbf6c835e,0xbec3ef15,0x3f800000,0x80000000,0x3f3daef9,0xbf2beb4a,
0x3dc8bd36,0xbf7ec46d,0xbf187fc0,0xbf4d9f02,0xbf7b14be,0xbe47c5c2,0xbf5b941a,0x3f039c3d,0xbe94a031,0x3f74fa0b,0x3edae880,0x3f676bd8,
0x3f800000,0x80000000,0x3f45e403,0xbf226799,0x3e47c5c2,0xbf7b14be,0xbef15aea,0xbf61c598,0xbf6c835e,0xbec3ef15,0xbf74fa0b,0x3e94a031,
0xbf0e39da,0x3f54db31,0x3dc8bd36,0x3f7ec46d,0x3f800000,0x80000000,0x3f4d9f02,0xbf187fc0,0x3e94a031,0xbf74fa0b,0xbeac7cd4,0xbf710908,
0xbf54db31,0xbf0e39da,0xbf7fb10f,0x3d48fb30,0xbf45e403,0x3f226799,0xbe78cfcc,0x3f7853f8,0x3f800000,0x80000000,0x3f54db31,0xbf0e39da,
0x3ec3ef15,0xbf6c835e,0xbe47c5c2,0xbf7b14be,0xbf3504f3,0xbf3504f3,0xbf7b14be,0xbe47c5c2,0xbf6c835e,0x3ec3ef15,0xbf0e39da,0x3f54db31,
0x3f800000,0x80000000,0x3f5b941a,0xbf039c3d,0x3ef15aea,0xbf61c598,0xbd48fb30,0xbf7fb10f,0xbf0e39da,0xbf54db31,0xbf676bd8,0xbedae880,
0xbf7ec46d,0x3dc8bd36,0xbf4d9f02,0x3f187fc0,0x3f800000,0x80000000,0x3f61c598,0xbef15aea,0x3f0e39da,0xbf54db31,0x3dc8bd36,0xbf7ec46d,
0xbec3ef15,0xbf6c835e,0xbf45e403,0xbf226799,0xbf7b14be,0xbe47c5c2,0xbf74fa0b,0x3e94a031,0x3f800000,0x80000000,0x3f676bd8,0xbedae880,
0x3f226799,0xbf45e403,0x3e78cfcc,0xbf7853f8,0xbe47c5c2,0xbf7b14be,0xbf187fc0,0xbf4d9f02,0xbf61c598,0xbef15aea,0xbf7fb10f,0xbd48fb30,
0x3f800000,0x80000000,0x3f800000,0x80000000,0x3f800000,0x80000000,0x3f800000,0x80000000,0x3f800000,0x80000000,0x3f800000,0x80000000,
0x3f800000,0x80000000,0x3f800000,0x80000000,0x3f7fec43,0xbcc90ab0,0x3f7f4e6d,0xbd96a905,0x3f7e1324,0xbdfab273,0x3f7c3b28,0xbe2f10a2,
0x3f79c79d,0xbe605c13,0x3f76ba07,0xbe888e93,0x3f731447,0xbea09ae5,0x3f6ed89e,0xbeb8442a,0x3f7fb10f,0xbd48fb30,0x3f7d3aac,0xbe164083,
0x3f7853f8,0xbe78cfcc,0x3f710908,0xbeac7cd4,0x3f676bd8,0xbedae880,0x3f5b941a,0xbf039c3d,0x3f4d9f02,0xbf187fc0,0x3f3daef9,0xbf2beb4a,
0x3f7f4e6d,0xbd96a905,0x3f79c79d,0xbe605c13,0x3f6ed89e,0xbeb8442a,0x3f5ebe05,0xbefc5d27,0x3f49d112,0xbf1d7fd1,0x3f3085bb,0xbf396842,
0x3f13682a,0xbf514d3d,0x3ee63375,0xbf64aa59,0x3f7ec46d,0xbdc8bd36,0x3f74fa0b,0xbe94a031,0x3f61c598,0xbef15aea,0x3f45e403,0xbf226799,
0x3f226799,0xbf45e403,0x3ef15aea,0xbf61c598,0x3e94a031,0xbf74fa0b,0x3dc8bd36,0xbf7ec46d,0x3f7e1324,0xbdfab273,0x3f6ed89e,0xbeb8442a,
0x3f514d3d,0xbf13682a,0x3f273656,0xbf41d870,0x3ee63375,0xbf64aa59,0x3e605c13,0xbf79c79d,0xbcc90ab0,0xbf7fec43,0xbe888e93,0xbf76ba07,
0x3f7d3aac,0xbe164083,0x3f676bd8,0xbedae880,0x3f3daef9,0xbf2beb4a,0x3f039c3d,0xbf5b941a,0x3e78cfcc,0xbf7853f8,0xbd48fb30,0xbf7fb10f,
0xbeac7cd4,0xbf710908,0xbf187fc0,0xbf4d9f02,0x3f7c3b28,0xbe2f10a2,0x3f5ebe05,0xbefc5d27,0x3f273656,0xbf41d870,0x3eb8442a,0xbf6ed89e,
0x3cc90ab0,0xbf7fec43,0xbea09ae5,0xbf731447,0xbf1d7fd1,0xbf49d112,0xbf584853,0xbf08f59b,0x3f7b14be,0xbe47c5c2,0x3f54db31,0xbf0e39da,
0x3f0e39da,0xbf54db31,0x3e47c5c2,0xbf7b14be,0xbe47c5c2,0xbf7b14be,0xbf0e39da,0xbf54db31,0xbf54db31,0xbf0e39da,0xbf7b14be,0xbe47c5c2,
0x3f6ed89e,0xbeb8442a,0x3ee63375,0xbf64aa59,0xbe888e93,0xbf76ba07,0xbf584853,0xbf08f59b,0xbf7c3b28,0x3e2f10a2,0xbf1d7fd1,0x3f49d112,
0x3d96a905,0x3f7f4e6d,0x3f396842,0x3f3085bb,0x3f710908,0xbeac7cd4,0x3f039c3d,0xbf5b941a,0xbe164083,0xbf7d3aac,0xbf3daef9,0xbf2beb4a,
0xbf7fb10f,0xbd48fb30,0xbf4d9f02,0x3f187fc0,0xbe78cfcc,0x3f7853f8,0x3edae880,0x3f676bd8,0x3f731447,0xbea09ae5,0x3f13682a,0xbf514d3d,
0xbcc90ab0,0xbf7fec43,0xbf1d7fd1,0xbf49d112,0xbf76ba07,0xbe888e93,0xbf6ed89e,0x3eb8442a,0xbf08f59b,0x3f584853,0x3d96a905,0x3f7f4e6d,
0x3f74fa0b,0xbe94a031,0x3f226799,0xbf45e403,0x3dc8bd36,0xbf7ec46d,0xbef15aea,0xbf61c598,0xbf61c598,0xbef15aea,0xbf7ec46d,0x3dc8bd36,
0xbf45e403,0x3f226799,0xbe94a031,0x3f74fa0b,0x3f76ba07,0xbe888e93,0x3f3085bb,0xbf396842,0x3e605c13,0xbf79c79d,0xbea09ae5,0xbf731447,
0xbf41d870,0xbf273656,0xbf7c3b28,0xbe2f10a2,0xbf6ed89e,0x3eb8442a,0xbf1d7fd1,0x3f49d112,0x3f7853f8,0xbe78cfcc,0x3f3daef9,0xbf2beb4a,
0x3eac7cd4,0xbf710908,0xbe164083,0xbf7d3aac,0xbf187fc0,0xbf4d9f02,0xbf676bd8,0xbedae880,0xbf7fb10f,0x3d48fb30,0xbf5b941a,0x3f039c3d,
0x3f79c79d,0xbe605c13,0x3f49d112,0xbf1d7fd1,0x3ee63375,0xbf64aa59,0x3cc90ab0,0xbf7fec43,0xbecf7bca,0xbf6a09a7,0xbf41d870,0xbf273656,
0xbf76ba07,0xbe888e93,0xbf7c3b28,0x3e2f10a2,0x3400,0x3400,0x3400,0x3400,0x3400,0x3400,0x3400,0x3400,
0x3400,0x3400,0x3400,0x3400,0x3400,0x3400,0x3400,0x3400,0x34000000,0x34000000,0x34000000,0x34000000,
0x34000000,0x34000000,0x34000000,0x34000000,0x34000000,0x34000000,0x34000000,0x34000000,0x34000000,0x34000000,0x34000000,0x34000000,
0x3400,0x31a831a8,0x2e1f3364,0x33642e1f,0x34000000,0x31a8b1a8,0x3364ae1f,0x2e1fb364,0xb400,0xb1a8b1a8,0xae1fb364,0xb364ae1f,
0xb4000000,0xb1a831a8,0xb3642e1f,0xae1f3364,0x34000000,0x31a8b1a8,0x3364ae1f,0x2e1fb364,0xb400,0xb1a8b1a8,0xae1fb364,0xb364ae1f,
0xb4000000,0xb1a831a8,0xb3642e1f,0xae1f3364,0x3400,0x31a831a8,0x2e1f3364,0x33642e1f,0x3400,0x34000000,0x31a831a8,0x31a8b1a8,
0xb400,0xb4000000,0xb1a8b1a8,0xb1a831a8,0x3400,0x34000000,0x31a831a8,0x31a8b1a8,0xb400,0xb4000000,0xb1a8b1a8,0xb1a831a8,
0x34000000,0xb400,0x31a8b1a8,0xb1a8b1a8,0xb4000000,0x3400,0xb1a831a8,0x31a831a8,0x34000000,0xb400,0x31a8b1a8,0xb1a8b1a8,
0xb4000000,0x3400,0xb1a831a8,0x31a831a8,0x3400,0x31a8b1a8,0x33642e1f,0xae1fb364,0xb4000000,0x31a831a8,0xae1f3364,0x3364ae1f,
0xb400,0xb1a831a8,0xb364ae1f,0x2e1f3364,0x34000000,0xb1a8b1a8,0x2e1fb364,0xb3642e1f,0x34000000,0xb1a8b1a8,0x2e1fb364,0xb3642e1f,
0x3400,0x31a8b1a8,0x33642e1f,0xae1fb364,0xb4000000,0x31a831a8,0xae1f3364,0x3364ae1f,0xb400,0xb1a831a8,0xb364ae1f,0x2e1f3364,
0x3400,0xb1a831a8,0xae1f3364,0xb3642e1f,0xb4000000,0xb1a8b1a8,0xb364ae1f,0xae1fb364,0xb400,0x31a8b1a8,0x2e1fb364,0x3364ae1f,
0x34000000,0x31a831a8,0x33642e1f,0x2e1f3364,0xb4000000,0xb1a8b1a8,0xb364ae1f,0xae1fb364,0xb400,0x31a8b1a8,0x2e1fb364,0x3364ae1f,
0x34000000,0x31a831a8,0x33642e1f,0x2e1f3364,0x3400,0xb1a831a8,0xae1f3364,0xb3642e1f,0x3400,0xb4000000,0xb1a831a8,0xb1a8b1a8,
0xb400,0x34000000,0x31a8b1a8,0x31a831a8,0x3400,0xb4000000,0xb1a831a8,0xb1a8b1a8,0xb400,0x34000000,0x31a8b1a8,0x31a831a8,
0xb4000000,0xb400,0xb1a8b1a8,0x31a8b1a8,0x34000000,0x3400,0x31a831a8,0xb1a831a8,0xb4000000,0xb400,0xb1a8b1a8,0x31a8b1a8,
0x34000000,0x3400,0x31a831a8,0xb1a831a8,0x3400,0xb1a8b1a8,0xb3642e1f,0x2e1fb364,0x34000000,0xb1a831a8,0x2e1f3364,0xb364ae1f,
0xb400,0x31a831a8,0x3364ae1f,0xae1f3364,0xb4000000,0x31a8b1a8,0xae1fb364,0x33642e1f,0xb4000000,0x31a8b1a8,0xae1fb364,0x33642e1f,
0x3400,0xb1a8b1a8,0xb3642e1f,0x2e1fb364,0x34000000,0xb1a831a8,0x2e1f3364,0xb364ae1f,0xb400,0x31a831a8,0x3364ae1f,0xae1f3364,
0x3400,0xb400,0xb4000000,0x34000000,0x3400,0xb400,0xb4000000,0x34000000,0x3400,0xb400,0xb4000000,0x34000000,
0x3400,0xb400,0xb4000000,0x34000000,0xb4000000,0x34000000,0xb400,0x3400,0xb4000000,0x34000000,0xb400,0x3400,
0xb4000000,0x34000000,0xb400,0x3400,0xb4000000,0x34000000,0xb400,0x3400,0x3400,0xb400,0x34000000,0xb4000000,
0x3400,0xb400,0x34000000,0xb4000000,0x3400,0xb400,0x34000000,0xb4000000,0x3400,0xb400,0x34000000,0xb4000000,
0x34000000,0xb4000000,0xb400,0x3400,0x34000000,0xb4000000,0xb400,0x3400,0x34000000,0xb4000000,0xb400,0x3400,
0x34000000,0xb4000000,0xb400,0x3400,0x3400,0xb1a8b1a8,0x3364ae1f,0xae1f3364,0x34000000,0xb1a831a8,0xae1fb364,0x33642e1f,
0xb400,0x31a831a8,0xb3642e1f,0x2e1fb364,0xb4000000,0x31a8b1a8,0x2e1f3364,0xb364ae1f,0x34000000,0xb1a831a8,0xae1fb364,0x33642e1f,
0xb400,0x31a831a8,0xb3642e1f,0x2e1fb364,0xb4000000,0x31a8b1a8,0x2e1f3364,0xb364ae1f,0x3400,0xb1a8b1a8,0x3364ae1f,0xae1f3364,
0x3400,0xb4000000,0x31a8b1a8,0x31a831a8,0xb400,0x34000000,0xb1a831a8,0xb1a8b1a8,0x3400,0xb4000000,0x31a8b1a8,0x31a831a8,
0xb400,0x34000000,0xb1a831a8,0xb1a8b1a8,0x34000000,0x3400,0xb1a8b1a8,0x31a8b1a8,0xb4000000,0xb400,0x31a831a8,0xb1a831a8,
0x34000000,0x3400,0xb1a8b1a8,0x31a8b1a8,0xb4000000,0xb400,0x31a831a8,0xb1a831a8,0x3400,0xb1a831a8,0x2e1fb364,0x3364ae1f,
0xb4000000,0xb1a8b1a8,0x33642e1f,0x2e1f3364,0xb400,0x31a8b1a8,0xae1f3364,0xb3642e1f,0x34000000,0x31a831a8,0xb364ae1f,0xae1fb364,
0x34000000,0x31a831a8,0xb364ae1f,0xae1fb364,0x3400,0xb1a831a8,0x2e1fb364,0x3364ae1f,0xb4000000,0xb1a8b1a8,0x33642e1f,0x2e1f3364,
0xb400,0x31a8b1a8,0xae1f3364,0xb3642e1f,0x3400,0x31a8b1a8,0xb364ae1f,0x2e1f3364,0xb4000000,0x31a831a8,0x2e1fb364,0xb3642e1f,
0xb400,0xb1a831a8,0x33642e1f,0xae1fb364,0x34000000,0xb1a8b1a8,0xae1f3364,0x3364ae1f,0xb4000000,0x31a831a8,0x2e1fb364,0xb3642e1f,
0xb400,0xb1a831a8,0x33642e1f,0xae1fb364,0x34000000,0xb1a8b1a8,0xae1f3364,0x3364ae1f,0x3400,0x31a8b1a8,0xb364ae1f,0x2e1f3364,
0x3400,0x34000000,0xb1a8b1a8,0xb1a831a8,0xb400,0xb4000000,0x31a831a8,0x31a8b1a8,0x3400,0x34000000,0xb1a8b1a8,0xb1a831a8,
0xb400,0xb4000000,0x31a831a8,0x31a8b1a8,0xb4000000,0x3400,0x31a8b1a8,0xb1a8b1a8,0x34000000,0xb400,0xb1a831a8,0x31a831a8,
0xb4000000,0x3400,0x31a8b1a8,0xb1a8b1a8,0x34000000,0xb400,0xb1a831a8,0x31a831a8,0x3400,0x31a831a8,0xae1fb364,0xb364ae1f,
0x34000000,0x31a8b1a8,0xb3642e1f,0xae1f3364,0xb400,0xb1a8b1a8,0x2e1f3364,0x33642e1f,0xb4000000,0xb1a831a8,0x3364ae1f,0x2e1fb364,
0xb4000000,0xb1a831a8,0x3364ae1f,0x2e1fb364,0x3400,0x31a831a8,0xae1fb364,0xb364ae1f,0x34000000,0x31a8b1a8,0xb3642e1f,0xae1f3364,
0xb400,0xb1a8b1a8,0x2e1f3364,0x33642e1f,0x3400,0x3400,0xb400,0xb400,0x3400,0x3400,0xb400,0xb400,
0x3400,0x3400,0xb400,0xb400,0x3400,0x3400,0xb400,0xb400,0xb4000000,0xb4000000,0x34000000,0x34000000,
0xb4000000,0xb4000000,0x34000000,0x34000000,0xb4000000,0xb4000000,0x34000000,0x34000000,0xb4000000,0xb4000000,0x34000000,0x34000000,
0x3e80,0x3e80,0x3e80,0xbdc43e6d,0x3e80,0xbdc43e6d,0x3e80,0xbe353e35,0x3e80,0xbe353e35,0x3e80,0xbe6d3dc4,
0x3e80,0xbe6d3dc4,0x3e80,0xbe800000,0x3e80,0x3e80,0xbe353e35,0xbe6d3dc4,0xbe353e35,0xbe6d3dc4,0xbe800000,0xbe35be35,
0xbe800000,0xbe35be35,0xbe35be35,0x3dc4be6d,0xbe35be35,0x3dc4be6d,0xbe80,0x3e800000,0x3e80,0x3e80,0xbe800000,0xbe6dbdc4,
0xbe800000,0xbe6dbdc4,0xbe80,0x3e35be35,0xbe80,0x3e35be35,0x3e800000,0x3dc43e6d,0x3e800000,0x3dc43e6d,0x3e80,0xbe800000,
0x3e80,0x3e80,0xbe35be35,0xbdc4be6d,0xbe35be35,0xbdc4be6d,0x3e800000,0x3e353e35,0x3e800000,0x3e353e35,0xbe353e35,0xbe6dbdc4,
0xbe353e35,0xbe6dbdc4,0xbe80,0x3e800000,0x3e80,0x3e80,0xbe80,0x3dc4be6d,0xbe80,0x3dc4be6d,0x3e80,0xbe353e35,
0x3e80,0xbe353e35,0xbe80,0x3e6dbdc4,0xbe80,0x3e6dbdc4,0x3e80,0xbe800000,0x3e80,0x3e80,0x3e35be35,0x3e6dbdc4,
0x3e35be35,0x3e6dbdc4,0xbe800000,0xbe35be35,0xbe800000,0xbe35be35,0x3e353e35,0xbdc43e6d,0x3e353e35,0xbdc43e6d,0xbe80,0x3e800000,
0x3e80,0x3e80,0x3e800000,0x3e6d3dc4,0x3e800000,0x3e6d3dc4,0xbe80,0x3e35be35,0xbe80,0x3e35be35,0xbe800000,0xbdc4be6d,
0xbe800000,0xbdc4be6d,0x3e80,0xbe800000,0x3e80,0x3e80,0x3e353e35,0x3dc43e6d,0x3e353e35,0x3dc43e6d,0x3e800000,0x3e353e35,
0x3e800000,0x3e353e35,0x3e35be35,0x3e6d3dc4,0x3e35be35,0x3e6d3dc4,0xbe80,0x3e800000,0x3e80,0xbe800000,0x3e80,0xbe6dbdc4,
0x3e80,0xbe6dbdc4,0x3e80,0xbe35be35,0x3e80,0xbe35be35,0x3e80,0xbdc4be6d,0x3e80,0xbdc4be6d,0x3e80,0xbe80,
0xbe80,0x3e800000,0x3e35be35,0x3dc43e6d,0x3e35be35,0x3dc43e6d,0x3e800000,0xbe353e35,0x3e800000,0xbe353e35,0x3e353e35,0xbe6dbdc4,
0x3e353e35,0xbe6dbdc4,0x3e80,0xbe80,0x3e80,0xbe800000,0xbe800000,0x3dc4be6d,0xbe800000,0x3dc4be6d,0xbe80,0x3e353e35,
0xbe80,0x3e353e35,0x3e800000,0xbe6d3dc4,0x3e800000,0xbe6d3dc4,0x3e80,0xbe80,0xbe80,0x3e800000,0x3e353e35,0xbe6d3dc4,
0x3e353e35,0xbe6d3dc4,0xbe800000,0x3e35be35,0xbe800000,0x3e35be35,0x3e35be35,0xbdc43e6d,0x3e35be35,0xbdc43e6d,0x3e80,0xbe80,
0x3e80,0xbe800000,0xbe80,0x3e6d3dc4,0xbe80,0x3e6d3dc4,0x3e80,0xbe35be35,0x3e80,0xbe35be35,0xbe80,0x3dc43e6d,
0xbe80,0x3dc43e6d,0x3e80,0xbe80,0xbe80,0x3e800000,0xbe353e35,0xbdc4be6d,0xbe353e35,0xbdc4be6d,0x3e800000,0xbe353e35,
0x3e800000,0xbe353e35,0xbe35be35,0x3e6d3dc4,0xbe35be35,0x3e6d3dc4,0x3e80,0xbe80,0x3e80,0xbe800000,0x3e800000,0xbdc43e6d,
0x3e800000,0xbdc43e6d,0xbe80,0x3e353e35,0xbe80,0x3e353e35,0xbe800000,0x3e6dbdc4,0xbe800000,0x3e6dbdc4,0x3e80,0xbe80,
0xbe80,0x3e800000,0xbe35be35,0x3e6dbdc4,0xbe35be35,0x3e6dbdc4,0xbe800000,0x3e35be35,0xbe800000,0x3e35be35,0xbe353e35,0x3dc4be6d,
0xbe353e35,0x3dc4be6d,0x3e80,0xbe80,0x3e800000,0x3e800000,0xbe800000,0xbe6dbdc4,0x3e800000,0x3e6d3dc4,0xbe800000,0xbe35be35,
0x3e800000,0x3e353e35,0xbe800000,0xbdc4be6d,0x3e800000,0x3dc43e6d,0xbe800000,0xbe80,0x3e800000,0x3e800000,0xbe35be35,0xbdc4be6d,
0x3e353e35,0x3dc43e6d,0xbe80,0x3e35be35,0x3e80,0xbe353e35,0x3e35be35,0x3e6d3dc4,0xbe353e35,0xbe6dbdc4,0x3e800000,0x3e80,
0x3e800000,0x3e800000,0xbe80,0x3dc4be6d,0x3e80,0xbdc43e6d,0x3e800000,0x3e353e35,0xbe800000,0xbe35be35,0x3e80,0xbe6d3dc4,
0xbe80,0x3e6dbdc4,0xbe800000,0xbe80,0x3e800000,0x3e800000,0x3e35be35,0x3e6dbdc4,0xbe353e35,0xbe6d3dc4,0x3e80,0xbe353e35,
0xbe80,0x3e35be35,0xbe35be35,0x3dc4be6d,0x3e353e35,0xbdc43e6d,0x3e800000,0x3e80,0x3e800000,0x3e800000,0x3e800000,0x3e6d3dc4,
0xbe800000,0xbe6dbdc4,0xbe800000,0xbe35be35,0x3e800000,0x3e353e35,0x3e800000,0x3dc43e6d,0xbe800000,0xbdc4be6d,0xbe800000,0xbe80,
0x3e800000,0x3e800000,0x3e353e35,0x3dc43e6d,0xbe35be35,0xbdc4be6d,0xbe80,0x3e35be35,0x3e80,0xbe353e35,0xbe353e35,0xbe6dbdc4,
0x3e35be35,0x3e6d3dc4,0x3e800000,0x3e80,0x3e800000,0x3e800000,0x3e80,0xbdc43e6d,0xbe80,0x3dc4be6d,0x3e800000,0x3e353e35,
0xbe800000,0xbe35be35,0xbe80,0x3e6dbdc4,0x3e80,0xbe6d3dc4,0xbe800000,0xbe80,0x3e800000,0x3e800000,0xbe353e35,0xbe6d3dc4,
0x3e35be35,0x3e6dbdc4,0x3e80,0xbe353e35,0xbe80,0x3e35be35,0x3e353e35,0xbdc43e6d,0xbe35be35,0x3dc4be6d,0x3e800000,0x3e80,
0x3e800000,0x3e80,0xbe800000,0x3dc4be6d,0x3e800000,0xbdc43e6d,0xbe800000,0x3e35be35,0x3e800000,0xbe353e35,0xbe800000,0x3e6dbdc4,
0x3e800000,0xbe6d3dc4,0xbe800000,0x3e800000,0xbe800000,0xbe80,0x3e353e35,0xbe6d3dc4,0xbe35be35,0x3e6dbdc4,0x3e80,0xbe35be35,
0xbe80,0x3e353e35,0xbe353e35,0x3dc4be6d,0x3e35be35,0xbdc43e6d,0xbe800000,0x3e800000,0x3e800000,0x3e80,0xbe80,0x3e6d3dc4,
0x3e80,0xbe6dbdc4,0x3e800000,0xbe353e35,0xbe800000,0x3e35be35,0x3e80,0xbdc4be6d,0xbe80,0x3dc43e6d,0xbe800000,0x3e800000,
0xbe800000,0xbe80,0xbe353e35,0xbdc4be6d,0x3e35be35,0x3dc43e6d,0xbe80,0x3e353e35,0x3e80,0xbe35be35,0x3e353e35,0xbe6dbdc4,
0xbe35be35,0x3e6d3dc4,0xbe800000,0x3e800000,0x3e800000,0x3e80,0x3e800000,0xbdc43e6d,0xbe800000,0x3dc4be6d,0xbe800000,0x3e35be35,
0x3e800000,0xbe353e35,0x3e800000,0xbe6d3dc4,0xbe800000,0x3e6dbdc4,0xbe800000,0x3e800000,0xbe800000,0xbe80,0xbe35be35,0x3e6dbdc4,
0x3e353e35,0xbe6d3dc4,0x3e80,0xbe35be35,0xbe80,0x3e353e35,0x3e35be35,0xbdc43e6d,0xbe353e35,0x3dc4be6d,0xbe800000,0x3e800000,
0x3e800000,0x3e80,0x3e80,0xbe6dbdc4,0xbe80,0x3e6d3dc4,0x3e800000,0xbe353e35,0xbe800000,0x3e35be35,0xbe80,0x3dc43e6d,
0x3e80,0xbdc4be6d,0xbe800000,0x3e800000,0xbe800000,0xbe80,0x3e35be35,0x3dc43e6d,0xbe353e35,0xbdc4be6d,0xbe80,0x3e353e35,
0x3e80,0xbe35be35,0xbe35be35,0x3e6d3dc4,0x3e353e35,0xbe6dbdc4,0xbe800000,0x3e800000,0x3f800000,0x0,0x3f800000,0x0,
0x3f800000,0x0,0x3f800000,0x0,0x3f800000,0x0,0x3f800000,0x0,0x3f800000,0x0,0x3f800000,0x0,
0x3f800000,0x0,0x3f7fb10f,0x3d48fb30,0x3f7ec46d,0x3dc8bd36,0x3f7d3aac,0x3e164083,0x3f7b14be,0x3e47c5c2,0x3f7853f8,0x3e78cfcc,
0x3f74fa0b,0x3e94a031,0x3f710908,0x3eac7cd4,0x3f800000,0x0,0x3f7ec46d,0x3dc8bd36,0x3f7b14be,0x3e47c5c2,0x3f74fa0b,0x3e94a031,
0x3f6c835e,0x3ec3ef15,0x3f61c598,0x3ef15aea,0x3f54db31,0x3f0e39da,0x3f45e403,0x3f226799,0x3f800000,0x0,0x3f7d3aac,0x3e164083,
0x3f74fa0b,0x3e94a031,0x3f676bd8,0x3edae880,0x3f54db31,0x3f0e39da,0x3f3daef9,0x3f2beb4a,0x3f226799,0x3f45e403,0x3f039c3d,0x3f5b941a,
0x3f800000,0x0,0x3f7b14be,0x3e47c5c2,0x3f6c835e,0x3ec3ef15,0x3f54db31,0x3f0e39da,0x3f3504f3,0x3f3504f3,0x3f0e39da,0x3f54db31,
0x3ec3ef15,0x3f6c835e,0x3e47c5c2,0x3f7b14be,0x3f800000,0x0,0x3f7853f8,0x3e78cfcc,0x3f61c598,0x3ef15aea,0x3f3daef9,0x3f2beb4a,
0x3f0e39da,0x3f54db31,0x3eac7cd4,0x3f710908,0x3dc8bd36,0x3f7ec46d,0xbe164083,0x3f7d3aac,0x3f800000,0x0,0x3f74fa0b,0x3e94a031,
0x3f54db31,0x3f0e39da,0x3f226799,0x3f45e403,0x3ec3ef15,0x3f6c835e,0x3dc8bd36,0x3f7ec46d,0xbe47c5c2,0x3f7b14be,0xbef15aea,0x3f61c598,
0x3f800000,0x0,0x3f710908,0x3eac7cd4,0x3f45e403,0x3f226799,0x3f039c3d,0x3f5b941a,0x3e47c5c2,0x3f7b14be,0xbe164083,0x3f7d3aac,
0xbef15aea,0x3f61c598,0xbf3daef9,0x3f2beb4a,0x3f800000,0x0,0x3f7fec43,0x3cc90ab0,0x3f7fb10f,0x3d48fb30,0x3f7f4e6d,0x3d96a905,
0x3f7ec46d,0x3dc8bd36,0x3f7e1324,0x3dfab273,0x3f7d3aac,0x3e164083,0x3f7c3b28,0x3e2f10a2,0x3f800000,0x0,0x3f7f4e6d,0x3d96a905,
0x3f7d3aac,0x3e164083,0x3f79c79d,0x3e605c13,0x3f74fa0b,0x3e94a031,0x3f6ed89e,0x3eb8442a,0x3f676bd8,0x3edae880,0x3f5ebe05,0x3efc5d27,
0x3f800000,0x0,0x3f7e1324,0x3dfab273,0x3f7853f8,0x3e78cfcc,0x3f6ed89e,0x3eb8442a,0x3f61c598,0x3ef15aea,0x3f514d3d,0x3f13682a,
0x3f3daef9,0x3f2beb4a,0x3f273656,0x3f41d870,0x3f800000,0x0,0x3f7c3b28,0x3e2f10a2,0x3f710908,0x3eac7cd4,0x3f5ebe05,0x3efc5d27,
0x3f45e403,0x3f226799,0x3f273656,0x3f41d870,0x3f039c3d,0x3f5b941a,0x3eb8442a,0x3f6ed89e,0x3f800000,0x0,0x3f79c79d,0x3e605c13,
0x3f676bd8,0x3edae880,0x3f49d112,0x3f1d7fd1,0x3f226799,0x3f45e403,0x3ee63375,0x3f64aa59,0x3e78cfcc,0x3f7853f8,0x3cc90ab0,0x3f7fec43,
0x3f800000,0x0,0x3f76ba07,0x3e888e93,0x3f5b941a,0x3f039c3d,0x3f3085bb,0x3f396842,0x3ef15aea,0x3f61c598,0x3e605c13,0x3f79c79d,
0xbd48fb30,0x3f7fb10f,0xbea09ae5,0x3f731447,0x3f800000,0x0,0x3f731447,0x3ea09ae5,0x3f4d9f02,0x3f187fc0,0x3f13682a,0x3f514d3d,
0x3e94a031,0x3f74fa0b,0xbcc90ab0,0x3f7fec43,0xbeac7cd4,0x3f710908,0xbf1d7fd1,0x3f49d112,0x3f800000,0x0,0x3f6ed89e,0x3eb8442a,
0x3f3daef9,0x3f2beb4a,0x3ee63375,0x3f64aa59,0x3dc8bd36,0x3f7ec46d,0xbe888e93,0x3f76ba07,0xbf187fc0,0x3f4d9f02,0xbf584853,0x3f08f59b,
0x3f800000,0x0,0x3f800000,0x0,0x3f800000,0x0,0x3f800000,0x0,0x3f800000,0x0,0x3f800000,0x0,
0x3f800000,0x0,0x3f800000,0x0,0x3f6c835e,0x3ec3ef15,0x3f3daef9,0x3f2beb4a,0x3f45e403,0x3f226799,0x3f4d9f02,0x3f187fc0,
0x3f54db31,0x3f0e39da,0x3f5b941a,0x3f039c3d,0x3f61c598,0x3ef15aea,0x3f676bd8,0x3edae880,0x3f3504f3,0x3f3504f3,0x3dc8bd36,0x3f7ec46d,
0x3e47c5c2,0x3f7b14be,0x3e94a031,0x3f74fa0b,0x3ec3ef15,0x3f6c835e,0x3ef15aea,0x3f61c598,0x3f0e39da,0x3f54db31,0x3f226799,0x3f45e403,
0x3ec3ef15,0x3f6c835e,0xbf187fc0,0x3f4d9f02,0xbef15aea,0x3f61c598,0xbeac7cd4,0x3f710908,0xbe47c5c2,0x3f7b14be,0xbd48fb30,0x3f7fb10f,
0x3dc8bd36,0x3f7ec46d,0x3e78cfcc,0x3f7853f8,0x248d3132,0x3f800000,0xbf7b14be,0x3e47c5c2,0xbf6c835e,0x3ec3ef15,0xbf54db31,0x3f0e39da,
0xbf3504f3,0x3f3504f3,0xbf0e39da,0x3f54db31,0xbec3ef15,0x3f6c835e,0xbe47c5c2,0x3f7b14be,0xbec3ef15,0x3f6c835e,0xbf5b941a,0xbf039c3d,
0xbf74fa0b,0xbe94a031,0xbf7fb10f,0xbd48fb30,0xbf7b14be,0x3e47c5c2,0xbf676bd8,0x3edae880,0xbf45e403,0x3f226799,0xbf187fc0,0x3f4d9f02,
0xbf3504f3,0x3f3504f3,0xbe94a031,0xbf74fa0b,0xbf0e39da,0xbf54db31,0xbf45e403,0xbf226799,0xbf6c835e,0xbec3ef15,0xbf7ec46d,0xbdc8bd36,
0xbf7b14be,0x3e47c5c2,0xbf61c598,0x3ef15aea,0xbf6c835e,0x3ec3ef15,0x3edae880,0xbf676bd8,0x3dc8bd36,0xbf7ec46d,0xbe78cfcc,0xbf7853f8,
0xbf0e39da,0xbf54db31,0xbf4d9f02,0xbf187fc0,0xbf74fa0b,0xbe94a031,0xbf7fb10f,0x3d48fb30,0x3f7b14be,0x3e47c5c2,0x3f6ed89e,0x3eb8442a,
0x3f710908,0x3eac7cd4,0x3f731447,0x3ea09ae5,0x3f74fa0b,0x3e94a031,0x3f76ba07,0x3e888e93,0x3f7853f8,0x3e78cfcc,0x3f79c79d,0x3e605c13,
0x3f54db31,0x3f0e39da,0x3ee63375,0x3f64aa59,0x3f039c3d,0x3f5b941a,0x3f13682a,0x3f514d3d,0x3f226799,0x3f45e403,0x3f3085bb,0x3f396842,
0x3f3daef9,0x3f2beb4a,0x3f49d112,0x3f1d7fd1,0x3f0e39da,0x3f54db31,0xbe888e93,0x3f76ba07,0xbe164083,0x3f7d3aac,0xbcc90ab0,0x3f7fec43,
0x3dc8bd36,0x3f7ec46d,0x3e605c13,0x3f79c79d,0x3eac7cd4,0x3f710908,0x3ee63375,0x3f64aa59,0x3e47c5c2,0x3f7b14be,0xbf584853,0x3f08f59b,
0xbf3daef9,0x3f2beb4a,0xbf1d7fd1,0x3f49d112,0xbef15aea,0x3f61c598,0xbea09ae5,0x3f731447,0xbe164083,0x3f7d3aac,0x3cc90ab0,0x3f7fec43,
0xbe47c5c2,0x3f7b14be,0xbf7c3b28,0xbe2f10a2,0xbf7fb10f,0x3d48fb30,0xbf76ba07,0x3e888e93,0xbf61c598,0x3ef15aea,0xbf41d870,0x3f273656,
0xbf187fc0,0x3f4d9f02,0xbecf7bca,0x3f6a09a7,0xbf0e39da,0x3f54db31,0xbf1d7fd1,0xbf49d112,0xbf4d9f02,0xbf187fc0,0xbf6ed89e,0xbeb8442a,
0xbf7ec46d,0xbdc8bd36,0xbf7c3b28,0x3e2f10a2,0xbf676bd8,0x3edae880,0xbf41d870,0x3f273656,0xbf54db31,0x3f0e39da,0x3d96a905,0xbf7f4e6d,
0xbe78cfcc,0xbf7853f8,0xbf08f59b,0xbf584853,0xbf45e403,0xbf226799,0xbf6ed89e,0xbeb8442a,0xbf7fb10f,0xbd48fb30,0xbf76ba07,0x3e888e93,
0xbf7b14be,0x3e47c5c2,0x3f396842,0xbf3085bb,0x3edae880,0xbf676bd8,0x3d96a905,0xbf7f4e6d,0xbe94a031,0xbf74fa0b,0xbf1d7fd1,0xbf49d112,
0xbf5b941a,0xbf039c3d,0xbf7c3b28,0xbe2f10a2,0x3e80,0x3e80,0x3e80,0x3e80,0x3e80,0x3e80,0x3e80,0x3e80,
0x3e80,0x3e80,0x3e80,0x3e80,0x3e80,0x3e80,0x3e80,0x3e80,0x3e800000,0x3e800000,0x3e800000,0x3e800000,
0x3e800000,0x3e800000,0x3e800000,0x3e800000,0x3e800000,0x3e800000,0x3e800000,0x3e800000,0x3e800000,0x3e800000,0x3e800000,0x3e800000,
0x3e80,0xbdc43e6d,0xbe80,0x3dc43e6d,0xbe353e35,0xbe6d3dc4,0x3e353e35,0x3e6d3dc4,0xbe800000,0xbe6dbdc4,0x3e800000,0x3e6dbdc4,
0xbe35be35,0xbdc4be6d,0x3e35be35,0x3dc4be6d,0x3e800000,0x3e6d3dc4,0xbe800000,0x3e6dbdc4,0x3e353e35,0x3dc43e6d,0x3e35be35,0x3dc4be6d,
0x3e80,0xbdc43e6d,0xbe80,0xbdc4be6d,0xbe353e35,0xbe6d3dc4,0xbe35be35,0xbe6dbdc4,0x3e80,0xbe353e35,0x3e80,0x3e353e35,
0xbe800000,0xbe35be35,0x3e800000,0x3e35be35,0xbe80,0x3e35be35,0xbe80,0xbe35be35,0x3e800000,0x3e353e35,0xbe800000,0xbe353e35,
0x3e800000,0x3e353e35,0x3e800000,0x3e35be35,0x3e80,0xbe353e35,0xbe80,0xbe35be35,0xbe800000,0xbe35be35,0xbe800000,0xbe353e35,
0xbe80,0x3e35be35,0x3e80,0x3e353e35,0x3e80,0xbe6d3dc4,0xbe80,0x3e6d3dc4,0xbe35be35,0x3dc4be6d,0x3e35be35,0xbdc4be6d,
0x3e800000,0x3dc43e6d,0xbe800000,0xbdc43e6d,0xbe353e35,0xbe6dbdc4,0x3e353e35,0x3e6dbdc4,0x3e800000,0x3dc43e6d,0xbe800000,0x3dc4be6d,
0xbe353e35,0xbe6dbdc4,0xbe35be35,0xbe6d3dc4,0xbe80,0x3e6dbdc4,0x3e80,0x3e6d3dc4,0x3e353e35,0xbdc43e6d,0x3e35be35,0xbdc4be6d,
0x3e80,0xbe800000,0x3e80,0x3e800000,0xbe80,0x3e800000,0xbe80,0xbe800000,0x3e80,0xbe800000,0x3e80,0x3e800000,
0xbe80,0x3e800000,0xbe80,0xbe800000,0x3e800000,0x3e80,0x3e800000,0xbe80,0xbe800000,0xbe80,0xbe800000,0x3e80,
0x3e800000,0x3e80,0x3e800000,0xbe80,0xbe800000,0xbe80,0xbe800000,0x3e80,0x3e80,0xbe6dbdc4,0xbe80,0x3e6dbdc4,
0x3e35be35,0x3dc43e6d,0xbe35be35,0xbdc43e6d,0xbe800000,0x3dc4be6d,0x3e800000,0xbdc4be6d,0x3e353e35,0xbe6d3dc4,0xbe353e35,0x3e6d3dc4,
0x3e800000,0xbdc43e6d,0xbe800000,0xbdc4be6d,0xbe35be35,0x3e6dbdc4,0xbe353e35,0x3e6d3dc4,0x3e80,0xbe6dbdc4,0xbe80,0xbe6d3dc4,
0x3e35be35,0x3dc43e6d,0x3e353e35,0x3dc4be6d,0x3e80,0xbe35be35,0x3e80,0x3e35be35,0x3e800000,0xbe353e35,0xbe800000,0x3e353e35,
0xbe80,0x3e353e35,0xbe80,0xbe353e35,0xbe800000,0x3e35be35,0x3e800000,0xbe35be35,0x3e800000,0xbe353e35,0x3e800000,0xbe35be35,
0xbe80,0x3e353e35,0x3e80,0x3e35be35,0xbe800000,0x3e35be35,0xbe800000,0x3e353e35,0x3e80,0xbe35be35,0xbe80,0xbe353e35,
0x3e80,0xbdc4be6d,0xbe80,0x3dc4be6d,0x3e353e35,0xbe6dbdc4,0xbe353e35,0x3e6dbdc4,0x3e800000,0xbe6d3dc4,0xbe800000,0x3e6d3dc4,
0x3e35be35,0xbdc43e6d,0xbe35be35,0x3dc43e6d,0x3e800000,0xbe6d3dc4,0xbe800000,0xbe6dbdc4,0x3e35be35,0xbdc43e6d,0x3e353e35,0xbdc4be6d,
0xbe80,0x3dc43e6d,0x3e80,0x3dc4be6d,0xbe35be35,0x3e6d3dc4,0xbe353e35,0x3e6dbdc4,0x3e80,0xbe80,0x3e80,0xbe80,
0x3e80,0xbe80,0x3e80,0xbe80,0x3e80,0xbe80,0x3e80,0xbe80,0x3e80,0xbe80,0x3e80,0xbe80,
0x3e800000,0xbe800000,0x3e800000,0xbe800000,0x3e800000,0xbe800000,0x3e800000,0xbe800000,0x3e800000,0xbe800000,0x3e800000,0xbe800000,
0x3e800000,0xbe800000,0x3e800000,0xbe800000,0x3e80,0x3dc4be6d,0xbe80,0xbdc4be6d,0xbe353e35,0x3e6dbdc4,0x3e353e35,0xbe6dbdc4,
0xbe800000,0x3e6d3dc4,0x3e800000,0xbe6d3dc4,0xbe35be35,0x3dc43e6d,0x3e35be35,0xbdc43e6d,0x3e800000,0xbe6dbdc4,0xbe800000,0xbe6d3dc4,
0x3e353e35,0xbdc4be6d,0x3e35be35,0xbdc43e6d,0x3e80,0x3dc4be6d,0xbe80,0x3dc43e6d,0xbe353e35,0x3e6dbdc4,0xbe35be35,0x3e6d3dc4,
0x3e80,0x3e35be35,0x3e80,0xbe35be35,0xbe800000,0x3e353e35,0x3e800000,0xbe353e35,0xbe80,0xbe353e35,0xbe80,0x3e353e35,
0x3e800000,0xbe35be35,0xbe800000,0x3e35be35,0x3e800000,0xbe35be35,0x3e800000,0xbe353e35,0x3e80,0x3e35be35,0xbe80,0x3e353e35,
0xbe800000,0x3e353e35,0xbe800000,0x3e35be35,0xbe80,0xbe353e35,0x3e80,0xbe35be35,0x3e80,0x3e6dbdc4,0xbe80,0xbe6dbdc4,
0xbe35be35,0xbdc43e6d,0x3e35be35,0x3dc43e6d,0x3e800000,0xbdc4be6d,0xbe800000,0x3dc4be6d,0xbe353e35,0x3e6d3dc4,0x3e353e35,0xbe6d3dc4,
0x3e800000,0xbdc4be6d,0xbe800000,0xbdc43e6d,0xbe353e35,0x3e6d3dc4,0xbe35be35,0x3e6dbdc4,0xbe80,0xbe6d3dc4,0x3e80,0xbe6dbdc4,
0x3e353e35,0x3dc4be6d,0x3e35be35,0x3dc43e6d,0x3e80,0x3e800000,0x3e80,0xbe800000,0xbe80,0xbe800000,0xbe80,0x3e800000,
0x3e80,0x3e800000,0x3e80,0xbe800000,0xbe80,0xbe800000,0xbe80,0x3e800000,0x3e800000,0xbe80,0x3e800000,0x3e80,
0xbe800000,0x3e80,0xbe800000,0xbe80,0x3e800000,0xbe80,0x3e800000,0x3e80,0xbe800000,0x3e80,0xbe800000,0xbe80,
0x3e80,0x3e6d3dc4,0xbe80,0xbe6d3dc4,0x3e35be35,0xbdc4be6d,0xbe35be35,0x3dc4be6d,0xbe800000,0xbdc43e6d,0x3e800000,0x3dc43e6d,
0x3e353e35,0x3e6dbdc4,0xbe353e35,0xbe6dbdc4,0x3e800000,0x3dc4be6d,0xbe800000,0x3dc43e6d,0xbe35be35,0xbe6d3dc4,0xbe353e35,0xbe6dbdc4,
0x3e80,0x3e6d3dc4,0xbe80,0x3e6dbdc4,0x3e35be35,0xbdc4be6d,0x3e353e35,0xbdc43e6d,0x3e80,0x3e353e35,0x3e80,0xbe353e35,
0x3e800000,0x3e35be35,0xbe800000,0xbe35be35,0xbe80,0xbe35be35,0xbe80,0x3e35be35,0xbe800000,0xbe353e35,0x3e800000,0x3e353e35,
0x3e800000,0x3e35be35,0x3e800000,0x3e353e35,0xbe80,0xbe35be35,0x3e80,0xbe353e35,0xbe800000,0xbe353e35,0xbe800000,0xbe35be35,
0x3e80,0x3e353e35,0xbe80,0x3e35be35,0x3e80,0x3dc43e6d,0xbe80,0xbdc43e6d,0x3e353e35,0x3e6d3dc4,0xbe353e35,0xbe6d3dc4,
0x3e800000,0x3e6dbdc4,0xbe800000,0xbe6dbdc4,0x3e35be35,0x3dc4be6d,0xbe35be35,0xbdc4be6d,0x3e800000,0x3e6dbdc4,0xbe800000,0x3e6d3dc4,
0x3e35be35,0x3dc4be6d,0x3e353e35,0x3dc43e6d,0xbe80,0xbdc4be6d,0x3e80,0xbdc43e6d,0xbe35be35,0xbe6dbdc4,0xbe353e35,0xbe6d3dc4,
0x3800,0x3800,0x3800,0x3800,0x3800,0x3800,0xb800,0xb800,0x3800,0x3800,0x3800,0x3800,
0x3800,0x3800,0xb800,0xb800,0x38000000,0x38000000,0x38000000,0x38000000,0x38000000,0x38000000,0xb8000000,0xb8000000,
0x38000000,0x38000000,0x38000000,0x38000000,0x38000000,0x38000000,0xb8000000,0xb8000000,0x3800,0xb800,0x3800,0xb800,
0x35a835a8,0xb5a8b5a8,0xb5a8b5a8,0x35a835a8,0x38000000,0xb8000000,0x38000000,0xb8000000,0x35a8b5a8,0xb5a835a8,0xb5a835a8,0x35a8b5a8,
0x38000000,0xb8000000,0x38000000,0xb8000000,0x35a8b5a8,0xb5a835a8,0xb5a835a8,0x35a8b5a8,0xb800,0x3800,0xb800,0x3800,
0xb5a8b5a8,0x35a835a8,0x35a835a8,0xb5a8b5a8,0x3800,0x3800,0x3800,0x3800,0x38000000,0x38000000,0xb8000000,0xb8000000,
0xb800,0xb800,0xb800,0xb800,0xb8000000,0xb8000000,0x38000000,0x38000000,0x38000000,0x38000000,0x38000000,0x38000000,
0xb800,0xb800,0x3800,0x3800,0xb8000000,0xb8000000,0xb8000000,0xb8000000,0x3800,0x3800,0xb800,0xb800,
0x3800,0xb800,0x3800,0xb800,0x35a8b5a8,0xb5a835a8,0xb5a835a8,0x35a8b5a8,0xb8000000,0x38000000,0xb8000000,0x38000000,
0x35a835a8,0xb5a8b5a8,0xb5a8b5a8,0x35a835a8,0x38000000,0xb8000000,0x38000000,0xb8000000,0xb5a8b5a8,0x35a835a8,0x35a835a8,0xb5a8b5a8,
0x3800,0xb800,0x3800,0xb800,0x35a8b5a8,0xb5a835a8,0xb5a835a8,0x35a8b5a8,0x3e80,0x3e80,0x3e80,0x3e80,
0x3e80,0x3e80,0xbe80,0xbe80,0x3e80,0x3e80,0x3e80,0x3e80,0x3e80,0x3e80,0xbe80,0xbe80,
0x3e800000,0x3e800000,0x3e800000,0x3e800000,0x3e800000,0x3e800000,0xbe800000,0xbe800000,0x3e800000,0x3e800000,0x3e800000,0x3e800000,
0x3e800000,0x3e800000,0xbe800000,0xbe800000,0x3e80,0xbe80,0x3e80,0xbe80,0xbe353e35,0x3e35be35,0x3e35be35,0xbe353e35,
0xbe800000,0x3e800000,0xbe800000,0x3e800000,0xbe35be35,0x3e353e35,0x3e353e35,0xbe35be35,0x3e800000,0xbe800000,0x3e800000,0xbe800000,
0x3e353e35,0xbe35be35,0xbe35be35,0x3e353e35,0x3e80,0xbe80,0x3e80,0xbe80,0xbe353e35,0x3e35be35,0x3e35be35,0xbe353e35,
0x3e80,0x3e80,0x3e80,0x3e80,0xbe800000,0xbe800000,0x3e800000,0x3e800000,0xbe80,0xbe80,0xbe80,0xbe80,
0x3e800000,0x3e800000,0xbe800000,0xbe800000,0x3e800000,0x3e800000,0x3e800000,0x3e800000,0x3e80,0x3e80,0xbe80,0xbe80,
0xbe800000,0xbe800000,0xbe800000,0xbe800000,0xbe80,0xbe80,0x3e80,0x3e80,0x3e80,0xbe80,0x3e80,0xbe80,
0xbe35be35,0x3e353e35,0x3e353e35,0xbe35be35,0x3e800000,0xbe800000,0x3e800000,0xbe800000,0xbe353e35,0x3e35be35,0x3e35be35,0xbe353e35,
0x3e800000,0xbe800000,0x3e800000,0xbe800000,0xbe353e35,0x3e35be35,0x3e35be35,0xbe353e35,0xbe80,0x3e80,0xbe80,0x3e80,
0x3e353e35,0xbe35be35,0xbe35be35,0x3e353e35,0x3400,0x3400,0x3400,0x3400,0x3400,0xb400,0x3400,0xb400,
0x3400,0x3400,0x3400,0x3400,0x3400,0xb400,0x3400,0xb400,0x3400,0x3400,0x34000000,0x34000000,
0x2e1f3364,0xae1fb364,0x3364ae1f,0xb3642e1f,0x31a831a8,0x31a831a8,0x31a8b1a8,0x31a8b1a8,0x33642e1f,0xb364ae1f,0x2e1fb364,0xae1f3364,
0x3400,0x3400,0xb400,0xb400,0x31a831a8,0xb1a8b1a8,0xb1a8b1a8,0x31a831a8,0x34000000,0x34000000,0xb4000000,0xb4000000,
0x31a8b1a8,0xb1a831a8,0xb1a831a8,0x31a8b1a8,0x3400,0x3400,0xb4000000,0xb4000000,0x33642e1f,0xb364ae1f,0xae1f3364,0x2e1fb364,
0x31a8b1a8,0x31a8b1a8,0x31a831a8,0x31a831a8,0xae1fb364,0x2e1f3364,0x3364ae1f,0xb3642e1f,0x3400,0x3400,0x3400,0x3400,
0x34000000,0xb4000000,0x34000000,0xb4000000,0xb400,0xb400,0xb400,0xb400,0xb4000000,0x34000000,0xb4000000,0x34000000,
0x3400,0x3400,0x34000000,0x34000000,0x3364ae1f,0xb3642e1f,0xae1fb364,0x2e1f3364,0xb1a8b1a8,0xb1a8b1a8,0xb1a831a8,0xb1a831a8,
0xae1f3364,0x2e1fb364,0x33642e1f,0xb364ae1f,0x3400,0x3400,0xb400,0xb400,0x31a8b1a8,0xb1a831a8,0xb1a831a8,0x31a8b1a8,
0xb4000000,0xb4000000,0x34000000,0x34000000,0x31a831a8,0xb1a8b1a8,0xb1a8b1a8,0x31a831a8,0x3400,0x3400,0xb4000000,0xb4000000,
0x2e1fb364,0xae1f3364,0x33642e1f,0xb364ae1f,0xb1a831a8,0xb1a831a8,0xb1a8b1a8,0xb1a8b1a8,0x3364ae1f,0xb3642e1f,0x2e1f3364,0xae1fb364,
0x3400,0x3400,0x3400,0x3400,0x3400,0xb400,0x3400,0xb400,0x3400,0x3400,0x3400,0x3400,
0x3400,0xb400,0x3400,0xb400,0xb400,0xb400,0xb4000000,0xb4000000,0xae1fb364,0x2e1f3364,0xb3642e1f,0x3364ae1f,
0xb1a8b1a8,0xb1a8b1a8,0xb1a831a8,0xb1a831a8,0xb364ae1f,0x33642e1f,0xae1f3364,0x2e1fb364,0x3400,0x3400,0xb400,0xb400,
0x31a831a8,0xb1a8b1a8,0xb1a8b1a8,0x31a831a8,0x34000000,0x34000000,0xb4000000,0xb4000000,0x31a8b1a8,0xb1a831a8,0xb1a831a8,0x31a8b1a8,
0xb400,0xb400,0x34000000,0x34000000,0xb364ae1f,0x33642e1f,0x2e1fb364,0xae1f3364,0xb1a831a8,0xb1a831a8,0xb1a8b1a8,0xb1a8b1a8,
0x2e1f3364,0xae1fb364,0xb3642e1f,0x3364ae1f,0x3400,0x3400,0x3400,0x3400,0x34000000,0xb4000000,0x34000000,0xb4000000,
0xb400,0xb400,0xb400,0xb400,0xb4000000,0x34000000,0xb4000000,0x34000000,0xb400,0xb400,0xb4000000,0xb4000000,
0xb3642e1f,0x3364ae1f,0x2e1f3364,0xae1fb364,0x31a831a8,0x31a831a8,0x31a8b1a8,0x31a8b1a8,0x2e1fb364,0xae1f3364,0xb364ae1f,0x33642e1f,
0x3400,0x3400,0xb400,0xb400,0x31a8b1a8,0xb1a831a8,0xb1a831a8,0x31a8b1a8,0xb4000000,0xb4000000,0x34000000,0x34000000,
0x31a831a8,0xb1a8b1a8,0xb1a8b1a8,0x31a831a8,0xb400,0xb400,0x34000000,0x34000000,0xae1f3364,0x2e1fb364,0xb364ae1f,0x33642e1f,
0x31a8b1a8,0x31a8b1a8,0x31a831a8,0x31a831a8,0xb3642e1f,0x3364ae1f,0xae1fb364,0x2e1f3364,0x34000000,0x34000000,0x34000000,0x34000000,
0x34000000,0xb4000000,0x34000000,0xb4000000,0x34000000,0x34000000,0x34000000,0x34000000,0x34000000,0xb4000000,0x34000000,0xb4000000,
0x34000000,0x34000000,0xb400,0xb400,0x3364ae1f,0xb3642e1f,0xae1fb364,0x2e1f3364,0x31a8b1a8,0x31a8b1a8,0xb1a8b1a8,0xb1a8b1a8,
0x2e1fb364,0xae1f3364,0xb364ae1f,0x33642e1f,0x34000000,0x34000000,0xb4000000,0xb4000000,0x31a8b1a8,0xb1a831a8,0xb1a831a8,0x31a8b1a8,
0xb400,0xb400,0x3400,0x3400,0xb1a8b1a8,0x31a831a8,0x31a831a8,0xb1a8b1a8,0x34000000,0x34000000,0x3400,0x3400,
0x2e1fb364,0xae1f3364,0x33642e1f,0xb364ae1f,0xb1a8b1a8,0xb1a8b1a8,0x31a8b1a8,0x31a8b1a8,0xb3642e1f,0x3364ae1f,0xae1fb364,0x2e1f3364,
0x34000000,0x34000000,0x34000000,0x34000000,0xb400,0x3400,0xb400,0x3400,0xb4000000,0xb4000000,0xb4000000,0xb4000000,
0x3400,0xb400,0x3400,0xb400,0x34000000,0x34000000,0xb400,0xb400,0xae1fb364,0x2e1f3364,0xb3642e1f,0x3364ae1f,
0xb1a831a8,0xb1a831a8,0x31a831a8,0x31a831a8,0x33642e1f,0xb364ae1f,0x2e1fb364,0xae1f3364,0x34000000,0x34000000,0xb4000000,0xb4000000,
0xb1a8b1a8,0x31a831a8,0x31a831a8,0xb1a8b1a8,0x3400,0x3400,0xb400,0xb400,0x31a8b1a8,0xb1a831a8,0xb1a831a8,0x31a8b1a8,
0x34000000,0x34000000,0x3400,0x3400,0xb364ae1f,0x33642e1f,0x2e1fb364,0xae1f3364,0x31a831a8,0x31a831a8,0xb1a831a8,0xb1a831a8,
0xae1fb364,0x2e1f3364,0x3364ae1f,0xb3642e1f,0x34000000,0x34000000,0x34000000,0x34000000,0x34000000,0xb4000000,0x34000000,0xb4000000,
0x34000000,0x34000000,0x34000000,0x34000000,0x34000000,0xb4000000,0x34000000,0xb4000000,0xb4000000,0xb4000000,0x3400,0x3400,
0xb3642e1f,0x3364ae1f,0x2e1f3364,0xae1fb364,0xb1a831a8,0xb1a831a8,0x31a831a8,0x31a831a8,0xae1f3364,0x2e1fb364,0x33642e1f,0xb364ae1f,
0x34000000,0x34000000,0xb4000000,0xb4000000,0x31a8b1a8,0xb1a831a8,0xb1a831a8,0x31a8b1a8,0xb400,0xb400,0x3400,0x3400,
0xb1a8b1a8,0x31a831a8,0x31a831a8,0xb1a8b1a8,0xb4000000,0xb4000000,0xb400,0xb400,0xae1f3364,0x2e1fb364,0xb364ae1f,0x33642e1f,
0x31a831a8,0x31a831a8,0xb1a831a8,0xb1a831a8,0x3364ae1f,0xb3642e1f,0x2e1f3364,0xae1fb364,0x34000000,0x34000000,0x34000000,0x34000000,
0xb400,0x3400,0xb400,0x3400,0xb4000000,0xb4000000,0xb4000000,0xb4000000,0x3400,0xb400,0x3400,0xb400,
0xb4000000,0xb4000000,0x3400,0x3400,0x2e1f3364,0xae1fb364,0x3364ae1f,0xb3642e1f,0x31a8b1a8,0x31a8b1a8,0xb1a8b1a8,0xb1a8b1a8,
0xb364ae1f,0x33642e1f,0xae1f3364,0x2e1fb364,0x34000000,0x34000000,0xb4000000,0xb4000000,0xb1a8b1a8,0x31a831a8,0x31a831a8,0xb1a8b1a8,
0x3400,0x3400,0xb400,0xb400,0x31a8b1a8,0xb1a831a8,0xb1a831a8,0x31a8b1a8,0xb4000000,0xb4000000,0xb400,0xb400,
0x33642e1f,0xb364ae1f,0xae1f3364,0x2e1fb364,0xb1a8b1a8,0xb1a8b1a8,0x31a8b1a8,0x31a8b1a8,0x2e1f3364,0xae1fb364,0xb3642e1f,0x3364ae1f,
0x3e80,0x3e80,0x3e80,0x3e80,0x3e80,0x3e80,0x3e80,0x3e80,0x3e80,0x3e80,0x3e80,0x3e80,
0x3e80,0x3e80,0x3e80,0x3e80,0x3e800000,0x3e800000,0x3e800000,0x3e800000,0x3e800000,0x3e800000,0x3e800000,0x3e800000,
0x3e800000,0x3e800000,0x3e800000,0x3e800000,0x3e800000,0x3e800000,0x3e800000,0x3e800000,0x3e80,0xbdc43e6d,0xbe80,0x3dc4be6d,
0xbe353e35,0xbe6d3dc4,0x3e35be35,0x3e6dbdc4,0xbe800000,0xbe6dbdc4,0x3e800000,0x3e6d3dc4,0xbe35be35,0xbdc4be6d,0x3e353e35,0x3dc43e6d,
0x3e800000,0x3e6d3dc4,0xbe800000,0xbe6dbdc4,0x3e353e35,0x3dc43e6d,0xbe35be35,0xbdc4be6d,0x3e80,0xbdc43e6d,0xbe80,0x3dc4be6d,
0xbe353e35,0xbe6d3dc4,0x3e35be35,0x3e6dbdc4,0x3e80,0xbe353e35,0x3e80,0xbe353e35,0xbe800000,0xbe35be35,0xbe800000,0xbe35be35,
0xbe80,0x3e35be35,0xbe80,0x3e35be35,0x3e800000,0x3e353e35,0x3e800000,0x3e353e35,0x3e800000,0x3e353e35,0x3e800000,0x3e353e35,
0x3e80,0xbe353e35,0x3e80,0xbe353e35,0xbe800000,0xbe35be35,0xbe800000,0xbe35be35,0xbe80,0x3e35be35,0xbe80,0x3e35be35,
0x3e80,0xbe6d3dc4,0xbe80,0x3e6dbdc4,0xbe35be35,0x3dc4be6d,0x3e353e35,0xbdc43e6d,0x3e800000,0x3dc43e6d,0xbe800000,0xbdc4be6d,
0xbe353e35,0xbe6dbdc4,0x3e35be35,0x3e6d3dc4,0x3e800000,0x3dc43e6d,0xbe800000,0xbdc4be6d,0xbe353e35,0xbe6dbdc4,0x3e35be35,0x3e6d3dc4,
0xbe80,0x3e6dbdc4,0x3e80,0xbe6d3dc4,0x3e353e35,0xbdc43e6d,0xbe35be35,0x3dc4be6d,0x3e80,0xbe800000,0x3e80,0xbe800000,
0xbe80,0x3e800000,0xbe80,0x3e800000,0x3e80,0xbe800000,0x3e80,0xbe800000,0xbe80,0x3e800000,0xbe80,0x3e800000,
0x3e800000,0x3e80,0x3e800000,0x3e80,0xbe800000,0xbe80,0xbe800000,0xbe80,0x3e800000,0x3e80,0x3e800000,0x3e80,
0xbe800000,0xbe80,0xbe800000,0xbe80,0x3e80,0xbe6dbdc4,0xbe80,0x3e6d3dc4,0x3e35be35,0x3dc43e6d,0xbe353e35,0xbdc4be6d,
0xbe800000,0x3dc4be6d,0x3e800000,0xbdc43e6d,0x3e353e35,0xbe6d3dc4,0xbe35be35,0x3e6dbdc4,0x3e800000,0xbdc43e6d,0xbe800000,0x3dc4be6d,
0xbe35be35,0x3e6dbdc4,0x3e353e35,0xbe6d3dc4,0x3e80,0xbe6dbdc4,0xbe80,0x3e6d3dc4,0x3e35be35,0x3dc43e6d,0xbe353e35,0xbdc4be6d,
0x3e80,0xbe35be35,0x3e80,0xbe35be35,0x3e800000,0xbe353e35,0x3e800000,0xbe353e35,0xbe80,0x3e353e35,0xbe80,0x3e353e35,
0xbe800000,0x3e35be35,0xbe800000,0x3e35be35,0x3e800000,0xbe353e35,0x3e800000,0xbe353e35,0xbe80,0x3e353e35,0xbe80,0x3e353e35,
0xbe800000,0x3e35be35,0xbe800000,0x3e35be35,0x3e80,0xbe35be35,0x3e80,0xbe35be35,0x3e80,0xbdc4be6d,0xbe80,0x3dc43e6d,
0x3e353e35,0xbe6dbdc4,0xbe35be35,0x3e6d3dc4,0x3e800000,0xbe6d3dc4,0xbe800000,0x3e6dbdc4,0x3e35be35,0xbdc43e6d,0xbe353e35,0x3dc4be6d,
0x3e800000,0xbe6d3dc4,0xbe800000,0x3e6dbdc4,0x3e35be35,0xbdc43e6d,0xbe353e35,0x3dc4be6d,0xbe80,0x3dc43e6d,0x3e80,0xbdc4be6d,
0xbe35be35,0x3e6d3dc4,0x3e353e35,0xbe6dbdc4,0x3e80,0xbe80,0x3e80,0xbe80,0x3e80,0xbe80,0x3e80,0xbe80,
0x3e80,0xbe80,0x3e80,0xbe80,0x3e80,0xbe80,0x3e80,0xbe80,0x3e800000,0xbe800000,0x3e800000,0xbe800000,
0x3e800000,0xbe800000,0x3e800000,0xbe800000,0x3e800000,0xbe800000,0x3e800000,0xbe800000,0x3e800000,0xbe800000,0x3e800000,0xbe800000,
0x3e80,0x3dc4be6d,0xbe80,0xbdc43e6d,0xbe353e35,0x3e6dbdc4,0x3e35be35,0xbe6d3dc4,0xbe800000,0x3e6d3dc4,0x3e800000,0xbe6dbdc4,
0xbe35be35,0x3dc43e6d,0x3e353e35,0xbdc4be6d,0x3e800000,0xbe6dbdc4,0xbe800000,0x3e6d3dc4,0x3e353e35,0xbdc4be6d,0xbe35be35,0x3dc43e6d,
0x3e80,0x3dc4be6d,0xbe80,0xbdc43e6d,0xbe353e35,0x3e6dbdc4,0x3e35be35,0xbe6d3dc4,0x3e80,0x3e35be35,0x3e80,0x3e35be35,
0xbe800000,0x3e353e35,0xbe800000,0x3e353e35,0xbe80,0xbe353e35,0xbe80,0xbe353e35,0x3e800000,0xbe35be35,0x3e800000,0xbe35be35,
0x3e800000,0xbe35be35,0x3e800000,0xbe35be35,0x3e80,0x3e35be35,0x3e80,0x3e35be35,0xbe800000,0x3e353e35,0xbe800000,0x3e353e35,
0xbe80,0xbe353e35,0xbe80,0xbe353e35,0x3e80,0x3e6dbdc4,0xbe80,0xbe6d3dc4,0xbe35be35,0xbdc43e6d,0x3e353e35,0x3dc4be6d,
0x3e800000,0xbdc4be6d,0xbe800000,0x3dc43e6d,0xbe353e35,0x3e6d3dc4,0x3e35be35,0xbe6dbdc4,0x3e800000,0xbdc4be6d,0xbe800000,0x3dc43e6d,
0xbe353e35,0x3e6d3dc4,0x3e35be35,0xbe6dbdc4,0xbe80,0xbe6d3dc4,0x3e80,0x3e6dbdc4,0x3e353e35,0x3dc4be6d,0xbe35be35,0xbdc43e6d,
0x3e80,0x3e800000,0x3e80,0x3e800000,0xbe80,0xbe800000,0xbe80,0xbe800000,0x3e80,0x3e800000,0x3e80,0x3e800000,
0xbe80,0xbe800000,0xbe80,0xbe800000,0x3e800000,0xbe80,0x3e800000,0xbe80,0xbe800000,0x3e80,0xbe800000,0x3e80,
0x3e800000,0xbe80,0x3e800000,0xbe80,0xbe800000,0x3e80,0xbe800000,0x3e80,0x3e80,0x3e6d3dc4,0xbe80,0xbe6dbdc4,
0x3e35be35,0xbdc4be6d,0xbe353e35,0x3dc43e6d,0xbe800000,0xbdc43e6d,0x3e800000,0x3dc4be6d,0x3e353e35,0x3e6dbdc4,0xbe35be35,0xbe6d3dc4,
0x3e800000,0x3dc4be6d,0xbe800000,0xbdc43e6d,0xbe35be35,0xbe6d3dc4,0x3e353e35,0x3e6dbdc4,0x3e80,0x3e6d3dc4,0xbe80,0xbe6dbdc4,
0x3e35be35,0xbdc4be6d,0xbe353e35,0x3dc43e6d,0x3e80,0x3e353e35,0x3e80,0x3e353e35,0x3e800000,0x3e35be35,0x3e800000,0x3e35be35,
0xbe80,0xbe35be35,0xbe80,0xbe35be35,0xbe800000,0xbe353e35,0xbe800000,0xbe353e35,0x3e800000,0x3e35be35,0x3e800000,0x3e35be35,
0xbe80,0xbe35be35,0xbe80,0xbe35be35,0xbe800000,0xbe353e35,0xbe800000,0xbe353e35,0x3e80,0x3e353e35,0x3e80,0x3e353e35,
0x3e80,0x3dc43e6d,0xbe80,0xbdc4be6d,0x3e353e35,0x3e6d3dc4,0xbe35be35,0xbe6dbdc4,0x3e800000,0x3e6dbdc4,0xbe800000,0xbe6d3dc4,
0x3e35be35,0x3dc4be6d,0xbe353e35,0xbdc43e6d,0x3e800000,0x3e6dbdc4,0xbe800000,0xbe6d3dc4,0x3e35be35,0x3dc4be6d,0xbe353e35,0xbdc43e6d,
0xbe80,0xbdc4be6d,0x3e80,0x3dc43e6d,0xbe35be35,0xbe6dbdc4,0x3e353e35,0x3e6d3dc4,0x3400,0x2e1f3364,0x3400,0x2e1f3364,
0x3400,0xae1fb364,0x3400,0xae1fb364,0x3400,0x2e1f3364,0x3400,0x2e1f3364,0x3400,0xae1fb364,0x3400,0xae1fb364,
0x224833fe,0x2ed7333b,0x33fea248,0x333baed7,0x2ed7333b,0xb1edb15f,0x333baed7,0xb15f31ed,0x31ed315f,0x33882d64,0x315fb1ed,0x2d64b388,
0x33882d64,0xb3fe2248,0x2d64b388,0x224833fe,0x264633f6,0x2f8b330e,0xa646b3f6,0xaf8bb30e,0x322f3113,0xb3a8aca5,0xb22fb113,0x33a82ca5,
0x33f6a646,0x330eaf8b,0xb3f62646,0xb30e2f8b,0x3113b22f,0xaca533a8,0xb113322f,0x2ca5b3a8,0x28b233ea,0x301d32dd,0xb3ea28b2,0xb2dd301d,
0x33c32bc6,0xb3ea28b2,0xabc633c3,0xa8b2b3ea,0x30c4b26d,0x2bc6b3c3,0x326d30c4,0x33c32bc6,0xb01db2dd,0x326d30c4,0x32ddb01d,0xb0c4326d,
0x2a3e33d9,0x307232a7,0x2a3e33d9,0x307232a7,0x33d9aa3e,0xb2a73072,0x33d9aa3e,0xb2a73072,0xaa3eb3d9,0xb072b2a7,0xaa3eb3d9,0xb072b2a7,
0xb3d92a3e,0x32a7b072,0xb3d92a3e,0x32a7b072,0x2bc633c3,0x30c4326d,0x33c3abc6,0x326db0c4,0x326db0c4,0xb01d32dd,0xb0c4b26d,0x32dd301d,
0xb2ddb01d,0xb3eaa8b2,0xb01d32dd,0xa8b233ea,0xa8b233ea,0xabc6b3c3,0x33ea28b2,0xb3c32bc6,0x2ca533a8,0x3113322f,0xaca5b3a8,0xb113b22f,
0x2f8bb30e,0xa64633f6,0xaf8b330e,0x2646b3f6,0xb3a82ca5,0xb22f3113,0x33a8aca5,0x322fb113,0x330e2f8b,0xb3f6a646,0xb30eaf8b,0x33f62646,
0x2d643388,0x315f31ed,0xb3882d64,0xb1ed315f,0x2248b3fe,0x2d643388,0x33fe2248,0xb3882d64,0xaed7333b,0xa24833fe,0xb33baed7,0xb3fea248,
0x31edb15f,0xaed7333b,0x315f31ed,0xb33baed7,0x3400,0x2e1f3364,0x3400,0x2e1f3364,0x3400,0xae1fb364,0x3400,0xae1fb364,
0x3400,0x2e1f3364,0x3400,0x2e1f3364,0x3400,0xae1fb364,0x3400,0xae1fb364,0xa248b3fe,0xaed7b33b,0xb3fe2248,0xb33b2ed7,
0xaed7b33b,0x31ed315f,0xb33b2ed7,0x315fb1ed,0xb1edb15f,0xb388ad64,0xb15f31ed,0xad643388,0xb388ad64,0x33fea248,0xad643388,0xa248b3fe,
0x264633f6,0x2f8b330e,0xa646b3f6,0xaf8bb30e,0x322f3113,0xb3a8aca5,0xb22fb113,0x33a82ca5,0x33f6a646,0x330eaf8b,0xb3f62646,0xb30e2f8b,
0x3113b22f,0xaca533a8,0xb113322f,0x2ca5b3a8,0xa8b2b3ea,0xb01db2dd,0x33eaa8b2,0x32ddb01d,0xb3c3abc6,0x33eaa8b2,0x2bc6b3c3,0x28b233ea,
0xb0c4326d,0xabc633c3,0xb26db0c4,0xb3c3abc6,0x301d32dd,0xb26db0c4,0xb2dd301d,0x30c4b26d,0x2a3e33d9,0x307232a7,0x2a3e33d9,0x307232a7,
0x33d9aa3e,0xb2a73072,0x33d9aa3e,0xb2a73072,0xaa3eb3d9,0xb072b2a7,0xaa3eb3d9,0xb072b2a7,0xb3d92a3e,0x32a7b072,0xb3d92a3e,0x32a7b072,
0xabc6b3c3,0xb0c4b26d,0xb3c32bc6,0xb26d30c4,0xb26d30c4,0x301db2dd,0x30c4326d,0xb2ddb01d,0x32dd301d,0x33ea28b2,0x301db2dd,0x28b2b3ea,
0x28b2b3ea,0x2bc633c3,0xb3eaa8b2,0x33c3abc6,0x2ca533a8,0x3113322f,0xaca5b3a8,0xb113b22f,0x2f8bb30e,0xa64633f6,0xaf8b330e,0x2646b3f6,
0xb3a82ca5,0xb22f3113,0x33a8aca5,0x322fb113,0x330e2f8b,0xb3f6a646,0xb30eaf8b,0x33f62646,0xad64b388,0xb15fb1ed,0x3388ad64,0x31edb15f,
0xa24833fe,0xad64b388,0xb3fea248,0x3388ad64,0x2ed7b33b,0x2248b3fe,0x333b2ed7,0x33fe2248,0xb1ed315f,0x2ed7b33b,0xb15fb1ed,0x333b2ed7,
0x34000000,0x3364ae1f,0x34000000,0x3364ae1f,0x34000000,0xb3642e1f,0x34000000,0xb3642e1f,0x34000000,0x3364ae1f,0x34000000,0x3364ae1f,
0x34000000,0xb3642e1f,0x34000000,0xb3642e1f,0x33fea248,0x333baed7,0xa248b3fe,0xaed7b33b,0x333baed7,0xb15f31ed,0xaed7b33b,0x31ed315f,
0x315fb1ed,0x2d64b388,0xb1edb15f,0xb388ad64,0x2d64b388,0x224833fe,0xb388ad64,0x33fea248,0x33f6a646,0x330eaf8b,0xb3f62646,0xb30e2f8b,
0x3113b22f,0xaca533a8,0xb113322f,0x2ca5b3a8,0xa646b3f6,0xaf8bb30e,0x264633f6,0x2f8b330e,0xb22fb113,0x33a82ca5,0x322f3113,0xb3a8aca5,
0x33eaa8b2,0x32ddb01d,0x28b233ea,0x301d32dd,0x2bc6b3c3,0x28b233ea,0x33c32bc6,0xb3ea28b2,0xb26db0c4,0xb3c3abc6,0x30c4b26d,0x2bc6b3c3,
0xb2dd301d,0x30c4b26d,0xb01db2dd,0x326d30c4,0x33d9aa3e,0x32a7b072,0x33d9aa3e,0x32a7b072,0xaa3eb3d9,0x307232a7,0xaa3eb3d9,0x307232a7,
0xb3d92a3e,0xb2a73072,0xb3d92a3e,0xb2a73072,0x2a3e33d9,0xb072b2a7,0x2a3e33d9,0xb072b2a7,0x33c3abc6,0x326db0c4,0xabc6b3c3,0xb0c4b26d,
0xb0c4b26d,0x32dd301d,0xb26d30c4,0x301db2dd,0xb01d32dd,0xa8b233ea,0x32dd301d,0x33ea28b2,0x33ea28b2,0xb3c32bc6,0x28b2b3ea,0x2bc633c3,
0x33a8aca5,0x322fb113,0xb3a82ca5,0xb22f3113,0xb30eaf8b,0x33f62646,0x330e2f8b,0xb3f6a646,0x2ca533a8,0x3113322f,0xaca5b3a8,0xb113b22f,
0x2f8bb30e,0xa64633f6,0xaf8b330e,0x2646b3f6,0x3388ad64,0x31edb15f,0x2d643388,0x315f31ed,0xb3fea248,0x3388ad64,0x2248b3fe,0x2d643388,
0x333b2ed7,0x33fe2248,0xaed7333b,0xa24833fe,0xb15fb1ed,0x333b2ed7,0x31edb15f,0xaed7333b,0x34000000,0x3364ae1f,0x34000000,0x3364ae1f,
0x34000000,0xb3642e1f,0x34000000,0xb3642e1f,0x34000000,0x3364ae1f,0x34000000,0x3364ae1f,0x34000000,0xb3642e1f,0x34000000,0xb3642e1f,
0xb3fe2248,0xb33b2ed7,0x224833fe,0x2ed7333b,0xb33b2ed7,0x315fb1ed,0x2ed7333b,0xb1edb15f,0xb15f31ed,0xad643388,0x31ed315f,0x33882d64,
0xad643388,0xa248b3fe,0x33882d64,0xb3fe2248,0x33f6a646,0x330eaf8b,0xb3f62646,0xb30e2f8b,0x3113b22f,0xaca533a8,0xb113322f,0x2ca5b3a8,
0xa646b3f6,0xaf8bb30e,0x264633f6,0x2f8b330e,0xb22fb113,0x33a82ca5,0x322f3113,0xb3a8aca5,0xb3ea28b2,0xb2dd301d,0xa8b2b3ea,0xb01db2dd,
0xabc633c3,0xa8b2b3ea,0xb3c3abc6,0x33eaa8b2,0x326d30c4,0x33c32bc6,0xb0c4326d,0xabc633c3,0x32ddb01d,0xb0c4326d,0x301d32dd,0xb26db0c4,
0x33d9aa3e,0x32a7b072,0x33d9aa3e,0x32a7b072,0xaa3eb3d9,0x307232a7,0xaa3eb3d9,0x307232a7,0xb3d92a3e,0xb2a73072,0xb3d92a3e,0xb2a73072,
0x2a3e33d9,0xb072b2a7,0x2a3e33d9,0xb072b2a7,0xb3c32bc6,0xb26d30c4,0x2bc633c3,0x30c4326d,0x30c4326d,0xb2ddb01d,0x326db0c4,0xb01d32dd,
0x301db2dd,0x28b2b3ea,0xb2ddb01d,0xb3eaa8b2,0xb3eaa8b2,0x33c3abc6,0xa8b233ea,0xabc6b3c3,0x33a8aca5,0x322fb113,0xb3a82ca5,0xb22f3113,
0xb30eaf8b,0x33f62646,0x330e2f8b,0xb3f6a646,0x2ca533a8,0x3113322f,0xaca5b3a8,0xb113b22f,0x2f8bb30e,0xa64633f6,0xaf8b330e,0x2646b3f6,
0xb3882d64,0xb1ed315f,0xad64b388,0xb15fb1ed,0x33fe2248,0xb3882d64,0xa24833fe,0xad64b388,0xb33baed7,0xb3fea248,0x2ed7b33b,0x2248b3fe,
0x315f31ed,0xb33baed7,0xb1ed315f,0x2ed7b33b,0x3e80,0xbc493e80,0xbdc43e6d,0xbddb3e67,0xbcc93e7f,0xbd163e7d,0xbdf13e62,0xbe043e5c,
0xbd483e7b,0xbd793e78,0xbe0e3e55,0xbe183e4e,0xbd953e75,0xbdac3e71,0xbe223e46,0xbe2c3e3e,0x3e800000,0x3e803c49,0x3e6d3dc4,0x3e673ddb,
0x3e7f3cc9,0x3e7d3d16,0x3e623df1,0x3e5c3e04,0x3e7b3d48,0x3e783d79,0x3e553e0e,0x3e4e3e18,0x3e753d95,0x3e713dac,0x3e463e22,0x3e3e3e2c,
0x3e80,0xbddb3e67,0x3dc4be6d,0x3e3ebe2c,0xbe463e22,0xbe783d79,0x3e75bd95,0x3e7d3d16,0xbe7bbd48,0xbe4ebe18,0x3e553e0e,0x3e043e5c,
0xbdf1be62,0xbc49be80,0x3cc93e7f,0xbdac3e71,0x3e800000,0x3e673ddb,0xbe6dbdc4,0xbe2cbe3e,0x3e223e46,0x3d793e78,0xbd95be75,0x3d16be7d,
0xbd483e7b,0xbe183e4e,0x3e0ebe55,0x3e5cbe04,0xbe623df1,0xbe803c49,0x3e7fbcc9,0x3e713dac,0x3e80,0xbe3e3e2c,0xbdc43e6d,0xbe713dac,
0xbe7fbcc9,0xbe18be4e,0xbe62bdf1,0xbd79be78,0x3d48be7b,0x3e5cbe04,0x3e0ebe55,0x3e7dbd16,0x3e753d95,0x3ddb3e67,0x3e463e22,0x3c493e80,
0x3e800000,0x3e2c3e3e,0x3e6d3dc4,0x3dac3e71,0xbcc93e7f,0xbe4e3e18,0xbdf13e62,0xbe783d79,0xbe7bbd48,0xbe04be5c,0xbe55be0e,0xbd16be7d,
0x3d95be75,0x3e67bddb,0x3e22be46,0x3e80bc49,0x3e80,0xbe713dac,0x3dc4be6d,0x3e803c49,0xbe22be46,0x3e04be5c,0x3d953e75,0xbe4e3e18,
0x3e7b3d48,0x3d163e7d,0xbe55be0e,0x3d79be78,0xbe623df1,0xbe3ebe2c,0x3e7fbcc9,0x3ddb3e67,0x3e800000,0x3dac3e71,0xbe6dbdc4,0x3c49be80,
0xbe463e22,0xbe5cbe04,0x3e75bd95,0x3e183e4e,0x3d48be7b,0x3e7dbd16,0xbe0e3e55,0xbe78bd79,0x3df13e62,0xbe2c3e3e,0xbcc9be7f,0x3e67bddb,
0x3e80,0xbe80bc49,0xbdc43e6d,0xbe67bddb,0x3cc9be7f,0x3e7d3d16,0x3df1be62,0x3e5c3e04,0xbd483e7b,0xbe78bd79,0xbe0e3e55,0xbe4ebe18,
0x3d95be75,0x3e713dac,0x3e22be46,0x3e3e3e2c,0x3e800000,0xbc493e80,0x3e6d3dc4,0xbddb3e67,0xbe7fbcc9,0x3d16be7d,0xbe62bdf1,0x3e04be5c,
0x3e7b3d48,0xbd793e78,0x3e553e0e,0xbe183e4e,0xbe75bd95,0x3dacbe71,0xbe46be22,0x3e2cbe3e,0x3e80,0xbe67bddb,0x3dc4be6d,0x3e2c3e3e,
0x3e46be22,0x3d793e78,0xbe753d95,0x3d16be7d,0xbe7bbd48,0x3e18be4e,0x3e553e0e,0xbe5c3e04,0x3df13e62,0xbe803c49,0xbcc9be7f,0x3e713dac,
0x3e800000,0xbddb3e67,0xbe6dbdc4,0x3e3ebe2c,0xbe22be46,0x3e78bd79,0x3d953e75,0xbe7dbd16,0xbd483e7b,0xbe4ebe18,0x3e0ebe55,0x3e043e5c,
0x3e62bdf1,0x3c493e80,0xbe7f3cc9,0x3dacbe71,0x3e80,0xbe2cbe3e,0xbdc43e6d,0xbdacbe71,0x3e7f3cc9,0xbe4e3e18,0x3e623df1,0xbe783d79,
0x3d48be7b,0x3e043e5c,0x3e0ebe55,0x3d163e7d,0xbe75bd95,0x3e67bddb,0xbe46be22,0x3e80bc49,0x3e800000,0xbe3e3e2c,0x3e6d3dc4,0xbe713dac,
0x3cc9be7f,0x3e183e4e,0x3df1be62,0x3d793e78,0xbe7bbd48,0x3e5cbe04,0xbe55be0e,0x3e7dbd16,0xbd953e75,0xbddbbe67,0xbe223e46,0xbc49be80,
0x3e80,0xbdacbe71,0x3dc4be6d,0xbc493e80,0x3e223e46,0xbe5cbe04,0xbd95be75,0x3e183e4e,0x3e7b3d48,0xbe7d3d16,0xbe55be0e,0x3e783d79,
0x3e62bdf1,0xbe2c3e3e,0xbe7f3cc9,0x3e67bddb,0x3e800000,0xbe713dac,0xbe6dbdc4,0x3e803c49,0x3e46be22,0xbe043e5c,0xbe753d95,0x3e4ebe18,
0x3d48be7b,0x3d163e7d,0xbe0e3e55,0x3d79be78,0xbdf1be62,0x3e3e3e2c,0x3cc93e7f,0xbddbbe67,0x3e80,0x3c49be80,0xbdc43e6d,0x3ddbbe67,
0xbcc93e7f,0x3d16be7d,0xbdf13e62,0x3e04be5c,0xbd483e7b,0x3d79be78,0xbe0e3e55,0x3e18be4e,0xbd953e75,0x3dacbe71,0xbe223e46,0x3e2cbe3e,
0x3e800000,0xbe80bc49,0x3e6d3dc4,0xbe67bddb,0x3e7f3cc9,0xbe7dbd16,0x3e623df1,0xbe5cbe04,0x3e7b3d48,0xbe78bd79,0x3e553e0e,0xbe4ebe18,
0x3e753d95,0xbe71bdac,0x3e463e22,0xbe3ebe2c,0x3e80,0x3ddbbe67,0x3dc4be6d,0xbe3e3e2c,0xbe463e22,0x3e78bd79,0x3e75bd95,0xbe7dbd16,
0xbe7bbd48,0x3e4e3e18,0x3e553e0e,0xbe04be5c,0xbdf1be62,0x3c493e80,0x3cc93e7f,0x3dacbe71,0x3e800000,0xbe67bddb,0xbe6dbdc4,0x3e2c3e3e,
0x3e223e46,0xbd79be78,0xbd95be75,0xbd163e7d,0xbd483e7b,0x3e18be4e,0x3e0ebe55,0xbe5c3e04,0xbe623df1,0x3e80bc49,0x3e7fbcc9,0xbe71bdac,
0x3e80,0x3e3ebe2c,0xbdc43e6d,0x3e71bdac,0xbe7fbcc9,0x3e183e4e,0xbe62bdf1,0x3d793e78,0x3d48be7b,0xbe5c3e04,0x3e0ebe55,0xbe7d3d16,
0x3e753d95,0xbddbbe67,0x3e463e22,0xbc49be80,0x3e800000,0xbe2cbe3e,0x3e6d3dc4,0xbdacbe71,0xbcc93e7f,0x3e4ebe18,0xbdf13e62,0x3e78bd79,
0xbe7bbd48,0x3e043e5c,0xbe55be0e,0x3d163e7d,0x3d95be75,0xbe673ddb,0x3e22be46,0xbe803c49,0x3e80,0x3e71bdac,0x3dc4be6d,0xbe80bc49,
0xbe22be46,0xbe043e5c,0x3d953e75,0x3e4ebe18,0x3e7b3d48,0xbd16be7d,0xbe55be0e,0xbd793e78,0xbe623df1,0x3e3e3e2c,0x3e7fbcc9,0xbddbbe67,
0x3e800000,0xbdacbe71,0xbe6dbdc4,0xbc493e80,0xbe463e22,0x3e5c3e04,0x3e75bd95,0xbe18be4e,0x3d48be7b,0xbe7d3d16,0xbe0e3e55,0x3e783d79,
0x3df13e62,0x3e2cbe3e,0xbcc9be7f,0xbe673ddb,0x3e80,0x3e803c49,0xbdc43e6d,0x3e673ddb,0x3cc9be7f,0xbe7dbd16,0x3df1be62,0xbe5cbe04,
0xbd483e7b,0x3e783d79,0xbe0e3e55,0x3e4e3e18,0x3d95be75,0xbe71bdac,0x3e22be46,0xbe3ebe2c,0x3e800000,0x3c49be80,0x3e6d3dc4,0x3ddbbe67,
0xbe7fbcc9,0xbd163e7d,0xbe62bdf1,0xbe043e5c,0x3e7b3d48,0x3d79be78,0x3e553e0e,0x3e18be4e,0xbe75bd95,0xbdac3e71,0xbe46be22,0xbe2c3e3e,
0x3e80,0x3e673ddb,0x3dc4be6d,0xbe2cbe3e,0x3e46be22,0xbd79be78,0xbe753d95,0xbd163e7d,0xbe7bbd48,0xbe183e4e,0x3e553e0e,0x3e5cbe04,
0x3df13e62,0x3e80bc49,0xbcc9be7f,0xbe71bdac,0x3e800000,0x3ddbbe67,0xbe6dbdc4,0xbe3e3e2c,0xbe22be46,0xbe783d79,0x3d953e75,0x3e7d3d16,
0xbd483e7b,0x3e4e3e18,0x3e0ebe55,0xbe04be5c,0x3e62bdf1,0xbc49be80,0xbe7f3cc9,0xbdac3e71,0x3e80,0x3e2c3e3e,0xbdc43e6d,0x3dac3e71,
0x3e7f3cc9,0x3e4ebe18,0x3e623df1,0x3e78bd79,0x3d48be7b,0xbe04be5c,0x3e0ebe55,0xbd16be7d,0xbe75bd95,0xbe673ddb,0xbe46be22,0xbe803c49,
0x3e800000,0x3e3ebe2c,0x3e6d3dc4,0x3e71bdac,0x3cc9be7f,0xbe18be4e,0x3df1be62,0xbd79be78,0xbe7bbd48,0xbe5c3e04,0xbe55be0e,0xbe7d3d16,
0xbd953e75,0x3ddb3e67,0xbe223e46,0x3c493e80,0x3e80,0x3dac3e71,0x3dc4be6d,0x3c49be80,0x3e223e46,0x3e5c3e04,0xbd95be75,0xbe18be4e,
0x3e7b3d48,0x3e7dbd16,0xbe55be0e,0xbe78bd79,0x3e62bdf1,0x3e2cbe3e,0xbe7f3cc9,0xbe673ddb,0x3e800000,0x3e71bdac,0xbe6dbdc4,0xbe80bc49,
0x3e46be22,0x3e04be5c,0xbe753d95,0xbe4e3e18,0x3d48be7b,0xbd16be7d,0xbe0e3e55,0xbd793e78,0xbdf1be62,0xbe3ebe2c,0x3cc93e7f,0x3ddb3e67,
0x3400,0x31a831a8,0x3400,0x31a831a8,0x3400,0xb1a8b1a8,0x3400,0xb1a8b1a8,0x3400,0x31a831a8,0x3400,0x31a831a8,
0x3400,0xb1a8b1a8,0x3400,0xb1a8b1a8,0x264633f6,0x322f3113,0x33f6a646,0x3113b22f,0x2f8b330e,0xb3a8aca5,0x330eaf8b,0xaca533a8,
0x322f3113,0x33f6a646,0x3113b22f,0xa646b3f6,0x33a82ca5,0xb30e2f8b,0x2ca5b3a8,0x2f8b330e,0x2a3e33d9,0x32a73072,0xaa3eb3d9,0xb2a7b072,
0x32a73072,0xb3d92a3e,0xb2a7b072,0x33d9aa3e,0x33d9aa3e,0x3072b2a7,0xb3d92a3e,0xb07232a7,0x3072b2a7,0x2a3e33d9,0xb07232a7,0xaa3eb3d9,
0x2ca533a8,0x330e2f8b,0xb3a82ca5,0xaf8b330e,0x33f62646,0xb22f3113,0xa64633f6,0xb113b22f,0x2f8bb30e,0xaca5b3a8,0x330e2f8b,0x33a8aca5,
0xb113b22f,0x33f62646,0x322fb113,0xa64633f6,0x2e1f3364,0x33642e1f,0x2e1f3364,0x33642e1f,0x3364ae1f,0xae1f3364,0x3364ae1f,0xae1f3364,
0xae1fb364,0xb364ae1f,0xae1fb364,0xb364ae1f,0xb3642e1f,0x2e1fb364,0xb3642e1f,0x2e1fb364,0x2f8b330e,0x33a82ca5,0x330eaf8b,0x2ca5b3a8,
0x3113b22f,0x264633f6,0xb22fb113,0x33f6a646,0xb3a8aca5,0xb30e2f8b,0xaca533a8,0x2f8b330e,0x264633f6,0xb22fb113,0x33f6a646,0xb113322f,
0x307232a7,0x33d92a3e,0xb072b2a7,0xb3d9aa3e,0x2a3eb3d9,0x307232a7,0xaa3e33d9,0xb072b2a7,0xb2a73072,0xaa3e33d9,0x32a7b072,0x2a3eb3d9,
0x33d92a3e,0xb2a73072,0xb3d9aa3e,0x32a7b072,0x3113322f,0x33f62646,0xb22f3113,0xa64633f6,0xaca5b3a8,0x330e2f8b,0x33a8aca5,0xaf8b330e,
0xa64633f6,0x3113322f,0xb3f6a646,0xb22f3113,0x2f8bb30e,0x2ca533a8,0x330e2f8b,0xb3a82ca5,0x3400,0x31a831a8,0x3400,0x31a831a8,
0x3400,0xb1a8b1a8,0x3400,0xb1a8b1a8,0x3400,0x31a831a8,0x3400,0x31a831a8,0x3400,0xb1a8b1a8,0x3400,0xb1a8b1a8,
0xa646b3f6,0xb22fb113,0xb3f62646,0xb113322f,0xaf8bb30e,0x33a82ca5,0xb30e2f8b,0x2ca5b3a8,0xb22fb113,0xb3f62646,0xb113322f,0x264633f6,
0xb3a8aca5,0x330eaf8b,0xaca533a8,0xaf8bb30e,0x2a3e33d9,0x32a73072,0xaa3eb3d9,0xb2a7b072,0x32a73072,0xb3d92a3e,0xb2a7b072,0x33d9aa3e,
0x33d9aa3e,0x3072b2a7,0xb3d92a3e,0xb07232a7,0x3072b2a7,0x2a3e33d9,0xb07232a7,0xaa3eb3d9,0xaca5b3a8,0xb30eaf8b,0x33a8aca5,0x2f8bb30e,
0xb3f6a646,0x322fb113,0x2646b3f6,0x3113322f,0xaf8b330e,0x2ca533a8,0xb30eaf8b,0xb3a82ca5,0x3113322f,0xb3f6a646,0xb22f3113,0x2646b3f6,
0x2e1f3364,0x33642e1f,0x2e1f3364,0x33642e1f,0x3364ae1f,0xae1f3364,0x3364ae1f,0xae1f3364,0xae1fb364,0xb364ae1f,0xae1fb364,0xb364ae1f,
0xb3642e1f,0x2e1fb364,0xb3642e1f,0x2e1fb364,0xaf8bb30e,0xb3a8aca5,0xb30e2f8b,0xaca533a8,0xb113322f,0xa646b3f6,0x322f3113,0xb3f62646,
0x33a82ca5,0x330eaf8b,0x2ca5b3a8,0xaf8bb30e,0xa646b3f6,0x322f3113,0xb3f62646,0x3113b22f,0x307232a7,0x33d92a3e,0xb072b2a7,0xb3d9aa3e,
0x2a3eb3d9,0x307232a7,0xaa3e33d9,0xb072b2a7,0xb2a73072,0xaa3e33d9,0x32a7b072,0x2a3eb3d9,0x33d92a3e,0xb2a73072,0xb3d9aa3e,0x32a7b072,
0xb113b22f,0xb3f6a646,0x322fb113,0x2646b3f6,0x2ca533a8,0xb30eaf8b,0xb3a82ca5,0x2f8bb30e,0x2646b3f6,0xb113b22f,0x33f62646,0x322fb113,
0xaf8b330e,0xaca5b3a8,0xb30eaf8b,0x33a8aca5,0x34000000,0x31a8b1a8,0x34000000,0x31a8b1a8,0x34000000,0xb1a831a8,0x34000000,0xb1a831a8,
0x34000000,0x31a8b1a8,0x34000000,0x31a8b1a8,0x34000000,0xb1a831a8,0x34000000,0xb1a831a8,0x33f6a646,0x3113b22f,0xa646b3f6,0xb22fb113,
0x330eaf8b,0xaca533a8,0xaf8bb30e,0x33a82ca5,0x3113b22f,0xa646b3f6,0xb22fb113,0xb3f62646,0x2ca5b3a8,0x2f8b330e,0xb3a8aca5,0x330eaf8b,
0x33d9aa3e,0x3072b2a7,0xb3d92a3e,0xb07232a7,0x3072b2a7,0x2a3e33d9,0xb07232a7,0xaa3eb3d9,0xaa3eb3d9,0xb2a7b072,0x2a3e33d9,0x32a73072,
0xb2a7b072,0x33d9aa3e,0x32a73072,0xb3d92a3e,0x33a8aca5,0x2f8bb30e,0x2ca533a8,0x330e2f8b,0x2646b3f6,0x3113322f,0x33f62646,0xb22f3113,
0xb30eaf8b,0xb3a82ca5,0x2f8bb30e,0xaca5b3a8,0xb22f3113,0x2646b3f6,0xb113b22f,0x33f62646,0x3364ae1f,0x2e1fb364,0x3364ae1f,0x2e1fb364,
0xae1fb364,0x33642e1f,0xae1fb364,0x33642e1f,0xb3642e1f,0xae1f3364,0xb3642e1f,0xae1f3364,0x2e1f3364,0xb364ae1f,0x2e1f3364,0xb364ae1f,
0x330eaf8b,0x2ca5b3a8,0xaf8bb30e,0xb3a8aca5,0xb22fb113,0x33f6a646,0xb113322f,0xa646b3f6,0xaca533a8,0x2f8b330e,0x33a82ca5,0x330eaf8b,
0x33f6a646,0xb113322f,0xa646b3f6,0x322f3113,0x32a7b072,0x2a3eb3d9,0xb2a73072,0xaa3e33d9,0xb3d9aa3e,0x32a7b072,0x33d92a3e,0xb2a73072,
0x307232a7,0x33d92a3e,0xb072b2a7,0xb3d9aa3e,0x2a3eb3d9,0x307232a7,0xaa3e33d9,0xb072b2a7,0x322fb113,0x2646b3f6,0x3113322f,0x33f62646,
0xb3a82ca5,0x2f8bb30e,0xaca5b3a8,0x330e2f8b,0x33f62646,0x322fb113,0xa64633f6,0x3113322f,0xb30eaf8b,0x33a8aca5,0x2f8bb30e,0x2ca533a8,
0x34000000,0x31a8b1a8,0x34000000,0x31a8b1a8,0x34000000,0xb1a831a8,0x34000000,0xb1a831a8,0x34000000,0x31a8b1a8,0x34000000,0x31a8b1a8,
0x34000000,0xb1a831a8,0x34000000,0xb1a831a8,0xb3f62646,0xb113322f,0x264633f6,0x322f3113,0xb30e2f8b,0x2ca5b3a8,0x2f8b330e,0xb3a8aca5,
0xb113322f,0x264633f6,0x322f3113,0x33f6a646,0xaca533a8,0xaf8bb30e,0x33a82ca5,0xb30e2f8b,0x33d9aa3e,0x3072b2a7,0xb3d92a3e,0xb07232a7,
0x3072b2a7,0x2a3e33d9,0xb07232a7,0xaa3eb3d9,0xaa3eb3d9,0xb2a7b072,0x2a3e33d9,0x32a73072,0xb2a7b072,0x33d9aa3e,0x32a73072,0xb3d92a3e,
0xb3a82ca5,0xaf8b330e,0xaca5b3a8,0xb30eaf8b,0xa64633f6,0xb113b22f,0xb3f6a646,0x322fb113,0x330e2f8b,0x33a8aca5,0xaf8b330e,0x2ca533a8,
0x322fb113,0xa64633f6,0x3113322f,0xb3f6a646,0x3364ae1f,0x2e1fb364,0x3364ae1f,0x2e1fb364,0xae1fb364,0x33642e1f,0xae1fb364,0x33642e1f,
0xb3642e1f,0xae1f3364,0xb3642e1f,0xae1f3364,0x2e1f3364,0xb364ae1f,0x2e1f3364,0xb364ae1f,0xb30e2f8b,0xaca533a8,0x2f8b330e,0x33a82ca5,
0x322f3113,0xb3f62646,0x3113b22f,0x264633f6,0x2ca5b3a8,0xaf8bb30e,0xb3a8aca5,0xb30e2f8b,0xb3f62646,0x3113b22f,0x264633f6,0xb22fb113,
0x32a7b072,0x2a3eb3d9,0xb2a73072,0xaa3e33d9,0xb3d9aa3e,0x32a7b072,0x33d92a3e,0xb2a73072,0x307232a7,0x33d92a3e,0xb072b2a7,0xb3d9aa3e,
0x2a3eb3d9,0x307232a7,0xaa3e33d9,0xb072b2a7,0xb22f3113,0xa64633f6,0xb113b22f,0xb3f6a646,0x33a8aca5,0xaf8b330e,0x2ca533a8,0xb30eaf8b,
0xb3f6a646,0xb22f3113,0x2646b3f6,0xb113b22f,0x330e2f8b,0xb3a82ca5,0xaf8b330e,0xaca5b3a8,0x3e80,0xbcc93e7f,0xbe353e35,0xbe463e22,
0xbd483e7b,0xbd953e75,0xbe553e0e,0xbe623df1,0xbdc43e6d,0xbdf13e62,0xbe6d3dc4,0xbe753d95,0xbe0e3e55,0xbe223e46,0xbe7b3d48,0xbe7f3cc9,
0x3e800000,0x3e7f3cc9,0x3e353e35,0x3e223e46,0x3e7b3d48,0x3e753d95,0x3e0e3e55,0x3df13e62,0x3e6d3dc4,0x3e623df1,0x3dc43e6d,0x3d953e75,
0x3e553e0e,0x3e463e22,0x3d483e7b,0x3cc93e7f,0x3e80,0xbdf13e62,0x3e35be35,0x3e75bd95,0xbe553e0e,0xbe7f3cc9,0x3e7b3d48,0x3e463e22,
0xbe6dbdc4,0xbe22be46,0x3dc43e6d,0xbcc93e7f,0xbd48be7b,0x3d95be75,0xbe0e3e55,0xbe623df1,0x3e800000,0x3e623df1,0xbe35be35,0xbd95be75,
0x3e0e3e55,0x3cc93e7f,0x3d48be7b,0x3e22be46,0xbdc43e6d,0xbe463e22,0x3e6dbdc4,0x3e7f3cc9,0xbe7b3d48,0xbe75bd95,0x3e553e0e,0x3df13e62,
0x3e80,0xbe463e22,0xbe353e35,0xbe7fbcc9,0xbe7bbd48,0xbdf1be62,0xbe0ebe55,0x3d95be75,0x3dc4be6d,0x3e75bd95,0x3e6dbdc4,0x3e623df1,
0x3e553e0e,0x3cc93e7f,0x3d483e7b,0xbe223e46,0x3e800000,0x3e223e46,0x3e353e35,0xbcc93e7f,0xbd483e7b,0xbe623df1,0xbe553e0e,0xbe75bd95,
0xbe6dbdc4,0xbd95be75,0xbdc4be6d,0x3df1be62,0x3e0ebe55,0x3e7fbcc9,0x3e7bbd48,0x3e463e22,0x3e80,0xbe753d95,0x3e35be35,0x3e623df1,
0xbe0ebe55,0x3e22be46,0xbd483e7b,0xbe7f3cc9,0x3e6d3dc4,0xbcc93e7f,0xbdc4be6d,0x3e46be22,0xbe7b3d48,0xbdf1be62,0x3e553e0e,0xbd953e75,
0x3e800000,0x3d953e75,0xbe35be35,0x3df1be62,0xbe553e0e,0xbe46be22,0x3e7b3d48,0x3cc93e7f,0x3dc4be6d,0x3e7f3cc9,0xbe6d3dc4,0xbe22be46,
0x3d483e7b,0xbe623df1,0x3e0ebe55,0x3e753d95,0x3e80,0xbe7fbcc9,0xbe353e35,0xbe22be46,0x3d48be7b,0x3e753d95,0x3e55be0e,0x3df13e62,
0xbdc43e6d,0xbe62bdf1,0xbe6d3dc4,0xbd95be75,0x3e0ebe55,0x3e463e22,0x3e7bbd48,0x3cc93e7f,0x3e800000,0xbcc93e7f,0x3e353e35,0xbe463e22,
0xbe7bbd48,0x3d95be75,0xbe0ebe55,0x3e62bdf1,0x3e6d3dc4,0xbdf13e62,0x3dc43e6d,0xbe753d95,0xbe55be0e,0x3e22be46,0xbd48be7b,0x3e7fbcc9,
0x3e80,0xbe62bdf1,0x3e35be35,0x3d953e75,0x3e55be0e,0x3cc93e7f,0xbe7bbd48,0x3e22be46,0xbe6dbdc4,0x3e46be22,0x3dc43e6d,0xbe7fbcc9,
0x3d483e7b,0xbe75bd95,0x3e0ebe55,0x3df13e62,0x3e800000,0xbdf13e62,0xbe35be35,0x3e75bd95,0xbe0ebe55,0x3e7fbcc9,0xbd483e7b,0xbe46be22,
0xbdc43e6d,0xbe22be46,0x3e6dbdc4,0xbcc93e7f,0x3e7bbd48,0xbd953e75,0xbe55be0e,0x3e62bdf1,0x3e80,0xbe22be46,0xbe353e35,0x3cc9be7f,
0x3e7b3d48,0xbe623df1,0x3e0e3e55,0xbe75bd95,0x3dc4be6d,0x3d953e75,0x3e6dbdc4,0xbdf13e62,0xbe55be0e,0x3e7fbcc9,0xbd48be7b,0x3e463e22,
0x3e800000,0xbe463e22,0x3e353e35,0xbe7fbcc9,0x3d48be7b,0x3df13e62,0x3e55be0e,0xbd953e75,0xbe6dbdc4,0x3e75bd95,0xbdc4be6d,0x3e623df1,
0xbe0e3e55,0xbcc9be7f,0xbe7b3d48,0x3e22be46,0x3e80,0xbd95be75,0x3e35be35,0xbdf13e62,0x3e0e3e55,0xbe46be22,0x3d48be7b,0x3cc93e7f,
0x3e6d3dc4,0xbe7fbcc9,0xbdc4be6d,0x3e223e46,0x3e7bbd48,0xbe623df1,0xbe55be0e,0x3e753d95,0x3e800000,0xbe753d95,0xbe35be35,0x3e623df1,
0x3e55be0e,0xbe223e46,0xbe7bbd48,0x3e7fbcc9,0x3dc4be6d,0xbcc93e7f,0xbe6d3dc4,0x3e46be22,0xbd48be7b,0x3df13e62,0xbe0e3e55,0x3d95be75,
0x3e80,0x3cc9be7f,0xbe353e35,0x3e46be22,0xbd483e7b,0x3d95be75,0xbe553e0e,0x3e62bdf1,0xbdc43e6d,0x3df1be62,0xbe6d3dc4,0x3e75bd95,
0xbe0e3e55,0x3e22be46,0xbe7b3d48,0x3e7fbcc9,0x3e800000,0xbe7fbcc9,0x3e353e35,0xbe22be46,0x3e7b3d48,0xbe75bd95,0x3e0e3e55,0xbdf1be62,
0x3e6d3dc4,0xbe62bdf1,0x3dc43e6d,0xbd95be75,0x3e553e0e,0xbe46be22,0x3d483e7b,0xbcc9be7f,0x3e80,0x3df1be62,0x3e35be35,0xbe753d95,
0xbe553e0e,0x3e7fbcc9,0x3e7b3d48,0xbe46be22,0xbe6dbdc4,0x3e223e46,0x3dc43e6d,0x3cc9be7f,0xbd48be7b,0xbd953e75,0xbe0e3e55,0x3e62bdf1,
0x3e800000,0xbe62bdf1,0xbe35be35,0x3d953e75,0x3e0e3e55,0xbcc9be7f,0x3d48be7b,0xbe223e46,0xbdc43e6d,0x3e46be22,0x3e6dbdc4,0xbe7fbcc9,
0xbe7b3d48,0x3e753d95,0x3e553e0e,0xbdf1be62,0x3e80,0x3e46be22,0xbe353e35,0x3e7f3cc9,0xbe7bbd48,0x3df13e62,0xbe0ebe55,0xbd953e75,
0x3dc4be6d,0xbe753d95,0x3e6dbdc4,0xbe62bdf1,0x3e553e0e,0xbcc9be7f,0x3d483e7b,0x3e22be46,0x3e800000,0xbe22be46,0x3e353e35,0x3cc9be7f,
0xbd483e7b,0x3e62bdf1,0xbe553e0e,0x3e753d95,0xbe6dbdc4,0x3d953e75,0xbdc4be6d,0xbdf13e62,0x3e0ebe55,0xbe7f3cc9,0x3e7bbd48,0xbe46be22,
0x3e80,0x3e75bd95,0x3e35be35,0xbe62bdf1,0xbe0ebe55,0xbe223e46,0xbd483e7b,0x3e7fbcc9,0x3e6d3dc4,0x3cc9be7f,0xbdc4be6d,0xbe463e22,
0xbe7b3d48,0x3df13e62,0x3e553e0e,0x3d95be75,0x3e800000,0xbd95be75,0xbe35be35,0xbdf13e62,0xbe553e0e,0x3e463e22,0x3e7b3d48,0xbcc9be7f,
0x3dc4be6d,0xbe7fbcc9,0xbe6d3dc4,0x3e223e46,0x3d483e7b,0x3e62bdf1,0x3e0ebe55,0xbe75bd95,0x3e80,0x3e7f3cc9,0xbe353e35,0x3e223e46,
0x3d48be7b,0xbe75bd95,0x3e55be0e,0xbdf1be62,0xbdc43e6d,0x3e623df1,0xbe6d3dc4,0x3d953e75,0x3e0ebe55,0xbe46be22,0x3e7bbd48,0xbcc9be7f,
0x3e800000,0x3cc9be7f,0x3e353e35,0x3e46be22,0xbe7bbd48,0xbd953e75,0xbe0ebe55,0xbe623df1,0x3e6d3dc4,0x3df1be62,0x3dc43e6d,0x3e75bd95,
0xbe55be0e,0xbe223e46,0xbd48be7b,0xbe7f3cc9,0x3e80,0x3e623df1,0x3e35be35,0xbd95be75,0x3e55be0e,0xbcc9be7f,0xbe7bbd48,0xbe223e46,
0xbe6dbdc4,0xbe463e22,0x3dc43e6d,0x3e7f3cc9,0x3d483e7b,0x3e753d95,0x3e0ebe55,0xbdf1be62,0x3e800000,0x3df1be62,0xbe35be35,0xbe753d95,
0xbe0ebe55,0xbe7f3cc9,0xbd483e7b,0x3e463e22,0xbdc43e6d,0x3e223e46,0x3e6dbdc4,0x3cc9be7f,0x3e7bbd48,0x3d95be75,0xbe55be0e,0xbe623df1,
0x3e80,0x3e223e46,0xbe353e35,0xbcc93e7f,0x3e7b3d48,0x3e62bdf1,0x3e0e3e55,0x3e753d95,0x3dc4be6d,0xbd95be75,0x3e6dbdc4,0x3df1be62,
0xbe55be0e,0xbe7f3cc9,0xbd48be7b,0xbe46be22,0x3e800000,0x3e46be22,0x3e353e35,0x3e7f3cc9,0x3d48be7b,0xbdf1be62,0x3e55be0e,0x3d95be75,
0xbe6dbdc4,0xbe753d95,0xbdc4be6d,0xbe62bdf1,0xbe0e3e55,0x3cc93e7f,0xbe7b3d48,0xbe223e46,0x3e80,0x3d953e75,0x3e35be35,0x3df1be62,
0x3e0e3e55,0x3e463e22,0x3d48be7b,0xbcc9be7f,0x3e6d3dc4,0x3e7f3cc9,0xbdc4be6d,0xbe22be46,0x3e7bbd48,0x3e62bdf1,0xbe55be0e,0xbe75bd95,
0x3e800000,0x3e75bd95,0xbe35be35,0xbe62bdf1,0x3e55be0e,0x3e22be46,0xbe7bbd48,0xbe7f3cc9,0x3dc4be6d,0x3cc9be7f,0xbe6d3dc4,0xbe463e22,
0xbd48be7b,0xbdf1be62,0xbe0e3e55,0xbd953e75,0x3400,0x33642e1f,0x3400,0x33642e1f,0x3400,0xb364ae1f,0x3400,0xb364ae1f,
0x3400,0x33642e1f,0x3400,0x33642e1f,0x3400,0xb364ae1f,0x3400,0xb364ae1f,0x28b233ea,0x33c32bc6,0x33eaa8b2,0x2bc6b3c3,
0x301d32dd,0xb3ea28b2,0x32ddb01d,0x28b233ea,0x326d30c4,0x32ddb01d,0x30c4b26d,0xb01db2dd,0x33c32bc6,0xb0c4326d,0x2bc6b3c3,0x326d30c4,
0x2ca533a8,0x33f62646,0xaca5b3a8,0xb3f6a646,0x330e2f8b,0xb22f3113,0xb30eaf8b,0x322fb113,0x33a8aca5,0x2646b3f6,0xb3a82ca5,0xa64633f6,
0x2f8bb30e,0x3113322f,0xaf8b330e,0xb113b22f,0x2ed7333b,0x33fea248,0xb33b2ed7,0x224833fe,0x33fea248,0xad643388,0x224833fe,0xb388ad64,
0x2d64b388,0xb1edb15f,0x33882d64,0x315fb1ed,0xb1edb15f,0x333baed7,0x315fb1ed,0x2ed7333b,0x307232a7,0x33d9aa3e,0x307232a7,0x33d9aa3e,
0x32a7b072,0x2a3e33d9,0x32a7b072,0x2a3e33d9,0xb072b2a7,0xb3d92a3e,0xb072b2a7,0xb3d92a3e,0xb2a73072,0xaa3eb3d9,0xb2a73072,0xaa3eb3d9,
0x315f31ed,0x3388ad64,0x31edb15f,0xad64b388,0x2ed7b33b,0x315f31ed,0xb33baed7,0x31edb15f,0xb3fea248,0xaed7333b,0xa24833fe,0x333b2ed7,
0x2d643388,0xb3fea248,0x3388ad64,0xa24833fe,0x322f3113,0x330eaf8b,0xb22fb113,0xb30e2f8b,0xa646b3f6,0x33a82ca5,0x264633f6,0xb3a8aca5,
0xb113322f,0x2f8b330e,0x3113b22f,0xaf8bb30e,0x33f6a646,0xaca533a8,0xb3f62646,0x2ca5b3a8,0x32dd301d,0x326db0c4,0xb01d32dd,0x30c4326d,
0xb0c4b26d,0x33c3abc6,0x326db0c4,0x2bc633c3,0x2bc633c3,0x33ea28b2,0xb3c32bc6,0xa8b233ea,0x28b2b3ea,0x32dd301d,0x33ea28b2,0xb01d32dd,
0x3400,0x33642e1f,0x3400,0x33642e1f,0x3400,0xb364ae1f,0x3400,0xb364ae1f,0x3400,0x33642e1f,0x3400,0x33642e1f,
0x3400,0xb364ae1f,0x3400,0xb364ae1f,0xa8b2b3ea,0xb3c3abc6,0xb3ea28b2,0xabc633c3,0xb01db2dd,0x33eaa8b2,0xb2dd301d,0xa8b2b3ea,
0xb26db0c4,0xb2dd301d,0xb0c4326d,0x301d32dd,0xb3c3abc6,0x30c4b26d,0xabc633c3,0xb26db0c4,0x2ca533a8,0x33f62646,0xaca5b3a8,0xb3f6a646,
0x330e2f8b,0xb22f3113,0xb30eaf8b,0x322fb113,0x33a8aca5,0x2646b3f6,0xb3a82ca5,0xa64633f6,0x2f8bb30e,0x3113322f,0xaf8b330e,0xb113b22f,
0xaed7b33b,0xb3fe2248,0x333baed7,0xa248b3fe,0xb3fe2248,0x2d64b388,0xa248b3fe,0x33882d64,0xad643388,0x31ed315f,0xb388ad64,0xb15f31ed,
0x31ed315f,0xb33b2ed7,0xb15f31ed,0xaed7b33b,0x307232a7,0x33d9aa3e,0x307232a7,0x33d9aa3e,0x32a7b072,0x2a3e33d9,0x32a7b072,0x2a3e33d9,
0xb072b2a7,0xb3d92a3e,0xb072b2a7,0xb3d92a3e,0xb2a73072,0xaa3eb3d9,0xb2a73072,0xaa3eb3d9,0xb15fb1ed,0xb3882d64,0xb1ed315f,0x2d643388,
0xaed7333b,0xb15fb1ed,0x333b2ed7,0xb1ed315f,0x33fe2248,0x2ed7b33b,0x2248b3fe,0xb33baed7,0xad64b388,0x33fe2248,0xb3882d64,0x2248b3fe,
0x322f3113,0x330eaf8b,0xb22fb113,0xb30e2f8b,0xa646b3f6,0x33a82ca5,0x264633f6,0xb3a8aca5,0xb113322f,0x2f8b330e,0x3113b22f,0xaf8bb30e,
0x33f6a646,0xaca533a8,0xb3f62646,0x2ca5b3a8,0xb2ddb01d,0xb26d30c4,0x301db2dd,0xb0c4b26d,0x30c4326d,0xb3c32bc6,0xb26d30c4,0xabc6b3c3,
0xabc6b3c3,0xb3eaa8b2,0x33c3abc6,0x28b2b3ea,0xa8b233ea,0xb2ddb01d,0xb3eaa8b2,0x301db2dd,0x34000000,0x2e1fb364,0x34000000,0x2e1fb364,
0x34000000,0xae1f3364,0x34000000,0xae1f3364,0x34000000,0x2e1fb364,0x34000000,0x2e1fb364,0x34000000,0xae1f3364,0x34000000,0xae1f3364,
0x33eaa8b2,0x2bc6b3c3,0xa8b2b3ea,0xb3c3abc6,0x32ddb01d,0x28b233ea,0xb01db2dd,0x33eaa8b2,0x30c4b26d,0xb01db2dd,0xb26db0c4,0xb2dd301d,
0x2bc6b3c3,0x326d30c4,0xb3c3abc6,0x30c4b26d,0x33a8aca5,0x2646b3f6,0xb3a82ca5,0xa64633f6,0x2f8bb30e,0x3113322f,0xaf8b330e,0xb113b22f,
0xaca5b3a8,0xb3f6a646,0x2ca533a8,0x33f62646,0xb30eaf8b,0x322fb113,0x330e2f8b,0xb22f3113,0x333baed7,0xa248b3fe,0x2ed7333b,0x33fea248,
0xa248b3fe,0x33882d64,0x33fea248,0xad643388,0xb388ad64,0xb15f31ed,0x2d64b388,0xb1edb15f,0xb15f31ed,0xaed7b33b,0xb1edb15f,0x333baed7,
0x32a7b072,0xaa3eb3d9,0x32a7b072,0xaa3eb3d9,0xb072b2a7,0x33d9aa3e,0xb072b2a7,0x33d9aa3e,0xb2a73072,0x2a3e33d9,0xb2a73072,0x2a3e33d9,
0x307232a7,0xb3d92a3e,0x307232a7,0xb3d92a3e,0x31edb15f,0xad64b388,0xb15fb1ed,0xb3882d64,0xb33baed7,0x31edb15f,0xaed7333b,0xb15fb1ed,
0xa24833fe,0x333b2ed7,0x33fe2248,0x2ed7b33b,0x3388ad64,0xa24833fe,0xad64b388,0x33fe2248,0x3113b22f,0xaf8bb30e,0xb113322f,0x2f8b330e,
0xb3f62646,0x2ca5b3a8,0x33f6a646,0xaca533a8,0x322f3113,0x330eaf8b,0xb22fb113,0xb30e2f8b,0xa646b3f6,0x33a82ca5,0x264633f6,0xb3a8aca5,
0x301db2dd,0xb0c4b26d,0x32dd301d,0x326db0c4,0xb26d30c4,0xabc6b3c3,0xb0c4b26d,0x33c3abc6,0x33c3abc6,0x28b2b3ea,0x2bc633c3,0x33ea28b2,
0xb3eaa8b2,0x301db2dd,0x28b2b3ea,0x32dd301d,0x34000000,0x2e1fb364,0x34000000,0x2e1fb364,0x34000000,0xae1f3364,0x34000000,0xae1f3364,
0x34000000,0x2e1fb364,0x34000000,0x2e1fb364,0x34000000,0xae1f3364,0x34000000,0xae1f3364,0xb3ea28b2,0xabc633c3,0x28b233ea,0x33c32bc6,
0xb2dd301d,0xa8b2b3ea,0x301d32dd,0xb3ea28b2,0xb0c4326d,0x301d32dd,0x326d30c4,0x32ddb01d,0xabc633c3,0xb26db0c4,0x33c32bc6,0xb0c4326d,
0x33a8aca5,0x2646b3f6,0xb3a82ca5,0xa64633f6,0x2f8bb30e,0x3113322f,0xaf8b330e,0xb113b22f,0xaca5b3a8,0xb3f6a646,0x2ca533a8,0x33f62646,
0xb30eaf8b,0x322fb113,0x330e2f8b,0xb22f3113,0xb33b2ed7,0x224833fe,0xaed7b33b,0xb3fe2248,0x224833fe,0xb388ad64,0xb3fe2248,0x2d64b388,
0x33882d64,0x315fb1ed,0xad643388,0x31ed315f,0x315fb1ed,0x2ed7333b,0x31ed315f,0xb33b2ed7,0x32a7b072,0xaa3eb3d9,0x32a7b072,0xaa3eb3d9,
0xb072b2a7,0x33d9aa3e,0xb072b2a7,0x33d9aa3e,0xb2a73072,0x2a3e33d9,0xb2a73072,0x2a3e33d9,0x307232a7,0xb3d92a3e,0x307232a7,0xb3d92a3e,
0xb1ed315f,0x2d643388,0x315f31ed,0x3388ad64,0x333b2ed7,0xb1ed315f,0x2ed7b33b,0x315f31ed,0x2248b3fe,0xb33baed7,0xb3fea248,0xaed7333b,
0xb3882d64,0x2248b3fe,0x2d643388,0xb3fea248,0x3113b22f,0xaf8bb30e,0xb113322f,0x2f8b330e,0xb3f62646,0x2ca5b3a8,0x33f6a646,0xaca533a8,
0x322f3113,0x330eaf8b,0xb22fb113,0xb30e2f8b,0xa646b3f6,0x33a82ca5,0x264633f6,0xb3a8aca5,0xb01d32dd,0x30c4326d,0xb2ddb01d,0xb26d30c4,
0x326db0c4,0x2bc633c3,0x30c4326d,0xb3c32bc6,0xb3c32bc6,0xa8b233ea,0xabc6b3c3,0xb3eaa8b2,0x33ea28b2,0xb01d32dd,0xa8b233ea,0xb2ddb01d,
0x3e80,0xbd163e7d,0xbe6d3dc4,0xbe783d79,0xbd953e75,0xbddb3e67,0xbe7f3cc9,0xbe80bc49,0xbe0e3e55,0xbe2c3e3e,0xbe7bbd48,0xbe71bdac,
0xbe463e22,0xbe5c3e04,0xbe62bdf1,0xbe4ebe18,0x3e800000,0x3e7d3d16,0x3dc43e6d,0x3d793e78,0x3e753d95,0x3e673ddb,0x3cc93e7f,0xbc493e80,
0x3e553e0e,0x3e3e3e2c,0xbd483e7b,0xbdac3e71,0x3e223e46,0x3e043e5c,0xbdf13e62,0xbe183e4e,0x3e80,0xbe043e5c,0x3e6dbdc4,0x3e7d3d16,
0xbe623df1,0xbe80bc49,0x3e463e22,0x3dac3e71,0xbe55be0e,0xbddbbe67,0xbd483e7b,0xbe2c3e3e,0x3cc9be7f,0x3e18be4e,0xbe753d95,0xbe78bd79,
0x3e800000,0x3e5c3e04,0xbdc4be6d,0x3d16be7d,0x3df13e62,0xbc493e80,0x3e22be46,0x3e71bdac,0xbe0e3e55,0xbe673ddb,0x3e7b3d48,0x3e3e3e2c,
0xbe7fbcc9,0xbe4ebe18,0x3d953e75,0xbd793e78,0x3e80,0xbe4e3e18,0xbe6d3dc4,0xbe5cbe04,0xbe75bd95,0xbdacbe71,0xbcc9be7f,0x3e3ebe2c,
0x3e0ebe55,0x3e80bc49,0x3e7b3d48,0x3ddb3e67,0x3e223e46,0xbd793e78,0xbdf13e62,0xbe7d3d16,0x3e800000,0x3e183e4e,0x3dc43e6d,0xbe043e5c,
0xbd953e75,0xbe713dac,0xbe7f3cc9,0xbe2cbe3e,0xbe55be0e,0xbc49be80,0x3d48be7b,0x3e67bddb,0x3e46be22,0x3e783d79,0x3e623df1,0x3d163e7d,
0x3e80,0xbe783d79,0x3e6dbdc4,0x3e183e4e,0xbdf1be62,0x3e3ebe2c,0xbe223e46,0xbe67bddb,0x3e553e0e,0xbdac3e71,0x3d48be7b,0x3e80bc49,
0xbe7fbcc9,0xbd16be7d,0x3d953e75,0xbe5c3e04,0x3e800000,0x3d793e78,0xbdc4be6d,0x3e4ebe18,0xbe623df1,0xbe2cbe3e,0x3e463e22,0xbddb3e67,
0x3e0ebe55,0x3e713dac,0xbe7bbd48,0xbc49be80,0xbcc93e7f,0xbe7d3d16,0x3e75bd95,0x3e043e5c,0x3e80,0xbe7dbd16,0xbe6d3dc4,0xbd79be78,
0x3d95be75,0x3e673ddb,0x3e7fbcc9,0xbc493e80,0xbe0e3e55,0xbe3ebe2c,0xbe7bbd48,0x3dacbe71,0x3e46be22,0x3e043e5c,0x3e623df1,0xbe183e4e,
0x3e800000,0xbd163e7d,0x3dc43e6d,0xbe783d79,0xbe75bd95,0x3ddbbe67,0xbcc9be7f,0x3e803c49,0x3e553e0e,0xbe2c3e3e,0xbd483e7b,0xbe71bdac,
0xbe22be46,0x3e5cbe04,0x3df1be62,0x3e4e3e18,0x3e80,0xbe5cbe04,0x3e6dbdc4,0xbd163e7d,0x3e62bdf1,0xbc493e80,0xbe46be22,0x3e71bdac,
0xbe55be0e,0x3e67bddb,0xbd483e7b,0xbe3ebe2c,0xbcc93e7f,0xbe4ebe18,0x3e75bd95,0xbd793e78,0x3e800000,0xbe043e5c,0xbdc4be6d,0x3e7d3d16,
0xbdf1be62,0x3e803c49,0xbe223e46,0xbdacbe71,0xbe0e3e55,0xbddbbe67,0x3e7b3d48,0xbe2c3e3e,0x3e7f3cc9,0xbe183e4e,0xbd95be75,0x3e783d79,
0x3e80,0xbe18be4e,0xbe6d3dc4,0x3e04be5c,0x3e753d95,0xbe713dac,0x3cc93e7f,0xbe2cbe3e,0x3e0ebe55,0x3c493e80,0x3e7b3d48,0xbe673ddb,
0xbe22be46,0x3e783d79,0x3df1be62,0x3d163e7d,0x3e800000,0xbe4e3e18,0x3dc43e6d,0xbe5cbe04,0x3d95be75,0x3dac3e71,0x3e7fbcc9,0xbe3e3e2c,
0xbe55be0e,0x3e80bc49,0x3d48be7b,0x3ddb3e67,0xbe463e22,0x3d79be78,0xbe62bdf1,0x3e7dbd16,0x3e80,0xbd79be78,0x3e6dbdc4,0xbe4e3e18,
0x3df13e62,0xbe2cbe3e,0x3e22be46,0xbddb3e67,0x3e553e0e,0xbe71bdac,0x3d48be7b,0x3c493e80,0x3e7f3cc9,0xbe7d3d16,0xbd95be75,0x3e043e5c,
0x3e800000,0xbe783d79,0xbdc4be6d,0x3e183e4e,0x3e62bdf1,0xbe3e3e2c,0xbe46be22,0x3e673ddb,0x3e0ebe55,0xbdac3e71,0xbe7bbd48,0x3e80bc49,
0x3cc9be7f,0x3d163e7d,0xbe753d95,0x3e5cbe04,0x3e80,0x3d16be7d,0xbe6d3dc4,0x3e78bd79,0xbd953e75,0x3ddbbe67,0xbe7f3cc9,0x3e803c49,
0xbe0e3e55,0x3e2cbe3e,0xbe7bbd48,0x3e713dac,0xbe463e22,0x3e5cbe04,0xbe62bdf1,0x3e4e3e18,0x3e800000,0xbe7dbd16,0x3dc43e6d,0xbd79be78,
0x3e753d95,0xbe67bddb,0x3cc93e7f,0x3c49be80,0x3e553e0e,0xbe3ebe2c,0xbd483e7b,0x3dacbe71,0x3e223e46,0xbe04be5c,0xbdf13e62,0x3e18be4e,
0x3e80,0x3e04be5c,0x3e6dbdc4,0xbe7dbd16,0xbe623df1,0x3e803c49,0x3e463e22,0xbdacbe71,0xbe55be0e,0x3ddb3e67,0xbd483e7b,0x3e2cbe3e,
0x3cc9be7f,0xbe183e4e,0xbe753d95,0x3e783d79,0x3e800000,0xbe5cbe04,0xbdc4be6d,0xbd163e7d,0x3df13e62,0x3c49be80,0x3e22be46,0xbe713dac,
0xbe0e3e55,0x3e67bddb,0x3e7b3d48,0xbe3ebe2c,0xbe7fbcc9,0x3e4e3e18,0x3d953e75,0x3d79be78,0x3e80,0x3e4ebe18,0xbe6d3dc4,0x3e5c3e04,
0xbe75bd95,0x3dac3e71,0xbcc9be7f,0xbe3e3e2c,0x3e0ebe55,0xbe803c49,0x3e7b3d48,0xbddbbe67,0x3e223e46,0x3d79be78,0xbdf13e62,0x3e7dbd16,
0x3e800000,0xbe18be4e,0x3dc43e6d,0x3e04be5c,0xbd953e75,0x3e71bdac,0xbe7f3cc9,0x3e2c3e3e,0xbe55be0e,0x3c493e80,0x3d48be7b,0xbe673ddb,
0x3e46be22,0xbe78bd79,0x3e623df1,0xbd16be7d,0x3e80,0x3e78bd79,0x3e6dbdc4,0xbe18be4e,0xbdf1be62,0xbe3e3e2c,0xbe223e46,0x3e673ddb,
0x3e553e0e,0x3dacbe71,0x3d48be7b,0xbe803c49,0xbe7fbcc9,0x3d163e7d,0x3d953e75,0x3e5cbe04,0x3e800000,0xbd79be78,0xbdc4be6d,0xbe4e3e18,
0xbe623df1,0x3e2c3e3e,0x3e463e22,0x3ddbbe67,0x3e0ebe55,0xbe71bdac,0xbe7bbd48,0x3c493e80,0xbcc93e7f,0x3e7dbd16,0x3e75bd95,0xbe04be5c,
0x3e80,0x3e7d3d16,0xbe6d3dc4,0x3d793e78,0x3d95be75,0xbe67bddb,0x3e7fbcc9,0x3c49be80,0xbe0e3e55,0x3e3e3e2c,0xbe7bbd48,0xbdac3e71,
0x3e46be22,0xbe04be5c,0x3e623df1,0x3e18be4e,0x3e800000,0x3d16be7d,0x3dc43e6d,0x3e78bd79,0xbe75bd95,0xbddb3e67,0xbcc9be7f,0xbe80bc49,
0x3e553e0e,0x3e2cbe3e,0xbd483e7b,0x3e713dac,0xbe22be46,0xbe5c3e04,0x3df1be62,0xbe4ebe18,0x3e80,0x3e5c3e04,0x3e6dbdc4,0x3d16be7d,
0x3e62bdf1,0x3c49be80,0xbe46be22,0xbe713dac,0xbe55be0e,0xbe673ddb,0xbd483e7b,0x3e3e3e2c,0xbcc93e7f,0x3e4e3e18,0x3e75bd95,0x3d79be78,
0x3e800000,0x3e04be5c,0xbdc4be6d,0xbe7dbd16,0xbdf1be62,0xbe80bc49,0xbe223e46,0x3dac3e71,0xbe0e3e55,0x3ddb3e67,0x3e7b3d48,0x3e2cbe3e,
0x3e7f3cc9,0x3e18be4e,0xbd95be75,0xbe78bd79,0x3e80,0x3e183e4e,0xbe6d3dc4,0xbe043e5c,0x3e753d95,0x3e71bdac,0x3cc93e7f,0x3e2c3e3e,
0x3e0ebe55,0xbc49be80,0x3e7b3d48,0x3e67bddb,0xbe22be46,0xbe78bd79,0x3df1be62,0xbd16be7d,0x3e800000,0x3e4ebe18,0x3dc43e6d,0x3e5c3e04,
0x3d95be75,0xbdacbe71,0x3e7fbcc9,0x3e3ebe2c,0xbe55be0e,0xbe803c49,0x3d48be7b,0xbddbbe67,0xbe463e22,0xbd793e78,0xbe62bdf1,0xbe7d3d16,
0x3e80,0x3d793e78,0x3e6dbdc4,0x3e4ebe18,0x3df13e62,0x3e2c3e3e,0x3e22be46,0x3ddbbe67,0x3e553e0e,0x3e713dac,0x3d48be7b,0xbc49be80,
0x3e7f3cc9,0x3e7dbd16,0xbd95be75,0xbe04be5c,0x3e800000,0x3e78bd79,0xbdc4be6d,0xbe18be4e,0x3e62bdf1,0x3e3ebe2c,0xbe46be22,0xbe67bddb,
0x3e0ebe55,0x3dacbe71,0xbe7bbd48,0xbe803c49,0x3cc9be7f,0xbd16be7d,0xbe753d95,0xbe5c3e04,0x3400,0x34000000,0x3400,0x34000000,
0x3400,0xb4000000,0x3400,0xb4000000,0x3400,0x34000000,0x3400,0x34000000,0x3400,0xb4000000,0x3400,0xb4000000,
0x2a3e33d9,0x33d9aa3e,0x33d9aa3e,0xaa3eb3d9,0x307232a7,0xb2a73072,0x32a7b072,0x307232a7,0x32a73072,0x3072b2a7,0x3072b2a7,0xb2a7b072,
0x33d92a3e,0xaa3e33d9,0x2a3eb3d9,0x33d92a3e,0x2e1f3364,0x3364ae1f,0xae1fb364,0xb3642e1f,0x33642e1f,0xae1f3364,0xb364ae1f,0x2e1fb364,
0x3364ae1f,0xae1fb364,0xb3642e1f,0x2e1f3364,0x2e1fb364,0x33642e1f,0xae1f3364,0xb364ae1f,0x307232a7,0x32a7b072,0xb2a73072,0x307232a7,
0x33d9aa3e,0x2a3e33d9,0x2a3e33d9,0xb3d92a3e,0x2a3eb3d9,0xb3d9aa3e,0x33d92a3e,0x2a3eb3d9,0xb2a7b072,0x3072b2a7,0x3072b2a7,0x32a73072,
0x31a831a8,0x31a8b1a8,0x31a831a8,0x31a8b1a8,0x31a8b1a8,0x31a831a8,0x31a8b1a8,0x31a831a8,0xb1a8b1a8,0xb1a831a8,0xb1a8b1a8,0xb1a831a8,
0xb1a831a8,0xb1a8b1a8,0xb1a831a8,0xb1a8b1a8,0x32a73072,0x3072b2a7,0x3072b2a7,0xb2a7b072,0x2a3eb3d9,0x33d92a3e,0xb3d9aa3e,0x2a3eb3d9,
0xb3d92a3e,0x2a3e33d9,0x2a3e33d9,0x33d9aa3e,0x307232a7,0xb2a73072,0x32a7b072,0x307232a7,0x33642e1f,0x2e1fb364,0xb364ae1f,0xae1f3364,
0xae1fb364,0x3364ae1f,0x2e1f3364,0xb3642e1f,0xae1f3364,0x33642e1f,0x2e1fb364,0xb364ae1f,0x3364ae1f,0x2e1f3364,0xb3642e1f,0xae1fb364,
0x33d92a3e,0x2a3eb3d9,0xaa3e33d9,0x33d92a3e,0xb2a7b072,0x3072b2a7,0x3072b2a7,0x32a73072,0x307232a7,0x32a7b072,0xb2a73072,0x307232a7,
0xaa3eb3d9,0x33d9aa3e,0x33d9aa3e,0x2a3e33d9,0x3400,0x34000000,0x3400,0x34000000,0x3400,0xb4000000,0x3400,0xb4000000,
0x3400,0x34000000,0x3400,0x34000000,0x3400,0xb4000000,0x3400,0xb4000000,0xaa3eb3d9,0xb3d92a3e,0xb3d92a3e,0x2a3e33d9,
0xb072b2a7,0x32a7b072,0xb2a73072,0xb072b2a7,0xb2a7b072,0xb07232a7,0xb07232a7,0x32a73072,0xb3d9aa3e,0x2a3eb3d9,0xaa3e33d9,0xb3d9aa3e,
0x2e1f3364,0x3364ae1f,0xae1fb364,0xb3642e1f,0x33642e1f,0xae1f3364,0xb364ae1f,0x2e1fb364,0x3364ae1f,0xae1fb364,0xb3642e1f,0x2e1f3364,
0x2e1fb364,0x33642e1f,0xae1f3364,0xb364ae1f,0xb072b2a7,0xb2a73072,0x32a7b072,0xb072b2a7,0xb3d92a3e,0xaa3eb3d9,0xaa3eb3d9,0x33d9aa3e,
0xaa3e33d9,0x33d92a3e,0xb3d9aa3e,0xaa3e33d9,0x32a73072,0xb07232a7,0xb07232a7,0xb2a7b072,0x31a831a8,0x31a8b1a8,0x31a831a8,0x31a8b1a8,
0x31a8b1a8,0x31a831a8,0x31a8b1a8,0x31a831a8,0xb1a8b1a8,0xb1a831a8,0xb1a8b1a8,0xb1a831a8,0xb1a831a8,0xb1a8b1a8,0xb1a831a8,0xb1a8b1a8,
0xb2a7b072,0xb07232a7,0xb07232a7,0x32a73072,0xaa3e33d9,0xb3d9aa3e,0x33d92a3e,0xaa3e33d9,0x33d9aa3e,0xaa3eb3d9,0xaa3eb3d9,0xb3d92a3e,
0xb072b2a7,0x32a7b072,0xb2a73072,0xb072b2a7,0x33642e1f,0x2e1fb364,0xb364ae1f,0xae1f3364,0xae1fb364,0x3364ae1f,0x2e1f3364,0xb3642e1f,
0xae1f3364,0x33642e1f,0x2e1fb364,0xb364ae1f,0x3364ae1f,0x2e1f3364,0xb3642e1f,0xae1fb364,0xb3d9aa3e,0xaa3e33d9,0x2a3eb3d9,0xb3d9aa3e,
0x32a73072,0xb07232a7,0xb07232a7,0xb2a7b072,0xb072b2a7,0xb2a73072,0x32a7b072,0xb072b2a7,0x2a3e33d9,0xb3d92a3e,0xb3d92a3e,0xaa3eb3d9,
0x34000000,0xb400,0x34000000,0xb400,0x34000000,0x3400,0x34000000,0x3400,0x34000000,0xb400,0x34000000,0xb400,
0x34000000,0x3400,0x34000000,0x3400,0x33d9aa3e,0xaa3eb3d9,0xaa3eb3d9,0xb3d92a3e,0x32a7b072,0x307232a7,0xb072b2a7,0x32a7b072,
0x3072b2a7,0xb2a7b072,0xb2a7b072,0xb07232a7,0x2a3eb3d9,0x33d92a3e,0xb3d9aa3e,0x2a3eb3d9,0x3364ae1f,0xae1fb364,0xb3642e1f,0x2e1f3364,
0x2e1fb364,0x33642e1f,0xae1f3364,0xb364ae1f,0xae1fb364,0xb3642e1f,0x2e1f3364,0x3364ae1f,0xb364ae1f,0x2e1fb364,0x33642e1f,0xae1f3364,
0x32a7b072,0xb072b2a7,0x307232a7,0x32a7b072,0xaa3eb3d9,0x33d9aa3e,0x33d9aa3e,0x2a3e33d9,0xb3d9aa3e,0xaa3e33d9,0x2a3eb3d9,0xb3d9aa3e,
0xb07232a7,0xb2a7b072,0xb2a7b072,0x3072b2a7,0x31a8b1a8,0xb1a8b1a8,0x31a8b1a8,0xb1a8b1a8,0xb1a8b1a8,0x31a8b1a8,0xb1a8b1a8,0x31a8b1a8,
0xb1a831a8,0x31a831a8,0xb1a831a8,0x31a831a8,0x31a831a8,0xb1a831a8,0x31a831a8,0xb1a831a8,0x3072b2a7,0xb2a7b072,0xb2a7b072,0xb07232a7,
0xb3d9aa3e,0x2a3eb3d9,0xaa3e33d9,0xb3d9aa3e,0x2a3e33d9,0x33d9aa3e,0x33d9aa3e,0xaa3eb3d9,0x32a7b072,0x307232a7,0xb072b2a7,0x32a7b072,
0x2e1fb364,0xb364ae1f,0xae1f3364,0x33642e1f,0xb3642e1f,0xae1fb364,0x3364ae1f,0x2e1f3364,0x33642e1f,0x2e1fb364,0xb364ae1f,0xae1f3364,
0xae1fb364,0x3364ae1f,0x2e1f3364,0xb3642e1f,0x2a3eb3d9,0xb3d9aa3e,0x33d92a3e,0x2a3eb3d9,0xb07232a7,0xb2a7b072,0xb2a7b072,0x3072b2a7,
0x32a7b072,0xb072b2a7,0x307232a7,0x32a7b072,0xb3d92a3e,0xaa3eb3d9,0xaa3eb3d9,0x33d9aa3e,0x34000000,0xb400,0x34000000,0xb400,
0x34000000,0x3400,0x34000000,0x3400,0x34000000,0xb400,0x34000000,0xb400,0x34000000,0x3400,0x34000000,0x3400,
0xb3d92a3e,0x2a3e33d9,0x2a3e33d9,0x33d9aa3e,0xb2a73072,0xb072b2a7,0x307232a7,0xb2a73072,0xb07232a7,0x32a73072,0x32a73072,0x3072b2a7,
0xaa3e33d9,0xb3d9aa3e,0x33d92a3e,0xaa3e33d9,0x3364ae1f,0xae1fb364,0xb3642e1f,0x2e1f3364,0x2e1fb364,0x33642e1f,0xae1f3364,0xb364ae1f,
0xae1fb364,0xb3642e1f,0x2e1f3364,0x3364ae1f,0xb364ae1f,0x2e1fb364,0x33642e1f,0xae1f3364,0xb2a73072,0x307232a7,0xb072b2a7,0xb2a73072,
0x2a3e33d9,0xb3d92a3e,0xb3d92a3e,0xaa3eb3d9,0x33d92a3e,0x2a3eb3d9,0xaa3e33d9,0x33d92a3e,0x3072b2a7,0x32a73072,0x32a73072,0xb07232a7,
0x31a8b1a8,0xb1a8b1a8,0x31a8b1a8,0xb1a8b1a8,0xb1a8b1a8,0x31a8b1a8,0xb1a8b1a8,0x31a8b1a8,0xb1a831a8,0x31a831a8,0xb1a831a8,0x31a831a8,
0x31a831a8,0xb1a831a8,0x31a831a8,0xb1a831a8,0xb07232a7,0x32a73072,0x32a73072,0x3072b2a7,0x33d92a3e,0xaa3e33d9,0x2a3eb3d9,0x33d92a3e,
0xaa3eb3d9,0xb3d92a3e,0xb3d92a3e,0x2a3e33d9,0xb2a73072,0xb072b2a7,0x307232a7,0xb2a73072,0x2e1fb364,0xb364ae1f,0xae1f3364,0x33642e1f,
0xb3642e1f,0xae1fb364,0x3364ae1f,0x2e1f3364,0x33642e1f,0x2e1fb364,0xb364ae1f,0xae1f3364,0xae1fb364,0x3364ae1f,0x2e1f3364,0xb3642e1f,
0xaa3e33d9,0x33d92a3e,0xb3d9aa3e,0xaa3e33d9,0x3072b2a7,0x32a73072,0x32a73072,0xb07232a7,0xb2a73072,0x307232a7,0xb072b2a7,0xb2a73072,
0x33d9aa3e,0x2a3e33d9,0x2a3e33d9,0xb3d92a3e,0x3e80,0xbd483e7b,0xbe800000,0xbe7bbd48,0xbdc43e6d,0xbe0e3e55,0xbe6dbdc4,0xbe55be0e,
0xbe353e35,0xbe553e0e,0xbe35be35,0xbe0ebe55,0xbe6d3dc4,0xbe7b3d48,0xbdc4be6d,0xbd48be7b,0x3e800000,0x3e7b3d48,0x3e80,0xbd483e7b,
0x3e6d3dc4,0x3e553e0e,0xbdc43e6d,0xbe0e3e55,0x3e353e35,0x3e0e3e55,0xbe353e35,0xbe553e0e,0x3dc43e6d,0x3d483e7b,0xbe6d3dc4,0xbe7b3d48,
0x3e80,0xbe0e3e55,0x3e800000,0x3e553e0e,0xbe6d3dc4,0xbe7bbd48,0x3dc43e6d,0xbd483e7b,0xbe35be35,0xbd48be7b,0xbe353e35,0xbe7b3d48,
0x3dc4be6d,0x3e55be0e,0xbe6dbdc4,0xbe0ebe55,0x3e800000,0x3e553e0e,0xbe80,0x3e0ebe55,0x3dc43e6d,0xbd483e7b,0x3e6dbdc4,0x3e7b3d48,
0xbe353e35,0xbe7b3d48,0x3e353e35,0x3d483e7b,0xbe6dbdc4,0xbe0ebe55,0xbdc43e6d,0xbe553e0e,0x3e80,0xbe553e0e,0xbe800000,0xbe0ebe55,
0xbe6dbdc4,0xbd48be7b,0x3dc4be6d,0x3e7bbd48,0x3e35be35,0x3e7b3d48,0x3e353e35,0xbd483e7b,0x3dc43e6d,0xbe0e3e55,0xbe6d3dc4,0xbe55be0e,
0x3e800000,0x3e0e3e55,0x3e80,0xbe553e0e,0xbdc43e6d,0xbe7b3d48,0xbe6dbdc4,0xbd48be7b,0xbe35be35,0x3d48be7b,0x3e35be35,0x3e7b3d48,
0x3e6dbdc4,0x3e553e0e,0x3dc43e6d,0xbe0e3e55,0x3e80,0xbe7b3d48,0x3e800000,0x3d483e7b,0xbdc4be6d,0x3e55be0e,0xbe6d3dc4,0xbe0ebe55,
0x3e353e35,0xbe0e3e55,0x3e35be35,0x3e553e0e,0xbe6dbdc4,0x3d48be7b,0xbdc43e6d,0xbe7bbd48,0x3e800000,0x3d483e7b,0xbe80,0x3e7bbd48,
0xbe6d3dc4,0xbe0ebe55,0x3dc43e6d,0xbe553e0e,0x3e35be35,0x3e553e0e,0xbe35be35,0x3e0ebe55,0xbdc43e6d,0xbe7bbd48,0x3e6d3dc4,0xbd483e7b,
0x3e80,0xbe7bbd48,0xbe800000,0x3d48be7b,0x3dc4be6d,0x3e553e0e,0x3e6d3dc4,0xbe0e3e55,0xbe353e35,0xbe0ebe55,0xbe35be35,0x3e55be0e,
0x3e6dbdc4,0x3d483e7b,0x3dc43e6d,0xbe7b3d48,0x3e800000,0xbd483e7b,0x3e80,0xbe7bbd48,0xbe6dbdc4,0x3e0ebe55,0x3dc4be6d,0x3e553e0e,
0x3e353e35,0xbe553e0e,0xbe353e35,0xbe0ebe55,0xbdc4be6d,0x3e7bbd48,0x3e6dbdc4,0x3d483e7b,0x3e80,0xbe55be0e,0x3e800000,0xbe0e3e55,
0x3e6dbdc4,0xbd483e7b,0xbdc4be6d,0x3e7b3d48,0xbe35be35,0x3e7bbd48,0xbe353e35,0xbd48be7b,0xbdc43e6d,0xbe0ebe55,0x3e6d3dc4,0xbe553e0e,
0x3e800000,0xbe0e3e55,0xbe80,0x3e553e0e,0xbdc4be6d,0x3e7b3d48,0xbe6d3dc4,0x3d48be7b,0xbe353e35,0xbd48be7b,0x3e353e35,0xbe7b3d48,
0x3e6d3dc4,0xbe553e0e,0x3dc4be6d,0x3e0e3e55,0x3e80,0xbe0ebe55,0xbe800000,0x3e55be0e,0x3e6d3dc4,0xbe7b3d48,0xbdc43e6d,0xbd48be7b,
0x3e35be35,0xbd483e7b,0x3e353e35,0xbe7bbd48,0xbdc4be6d,0x3e553e0e,0x3e6dbdc4,0xbe0e3e55,0x3e800000,0xbe553e0e,0x3e80,0xbe0ebe55,
0x3dc4be6d,0x3d483e7b,0x3e6d3dc4,0xbe7b3d48,0xbe35be35,0x3e7b3d48,0x3e35be35,0xbd483e7b,0xbe6d3dc4,0x3e0ebe55,0xbdc4be6d,0x3e553e0e,
0x3e80,0xbd48be7b,0x3e800000,0xbe7b3d48,0x3dc43e6d,0xbe0ebe55,0x3e6dbdc4,0xbe553e0e,0x3e353e35,0xbe55be0e,0x3e35be35,0xbe0e3e55,
0x3e6d3dc4,0xbe7bbd48,0x3dc4be6d,0xbd483e7b,0x3e800000,0xbe7b3d48,0xbe80,0x3d483e7b,0x3e6dbdc4,0xbe553e0e,0xbdc4be6d,0x3e0e3e55,
0x3e35be35,0xbe0e3e55,0xbe35be35,0x3e553e0e,0x3dc4be6d,0xbd483e7b,0xbe6dbdc4,0x3e7b3d48,0x3e80,0x3d48be7b,0xbe800000,0x3e7b3d48,
0xbdc43e6d,0x3e0ebe55,0xbe6dbdc4,0x3e553e0e,0xbe353e35,0x3e55be0e,0xbe35be35,0x3e0e3e55,0xbe6d3dc4,0x3e7bbd48,0xbdc4be6d,0x3d483e7b,
0x3e800000,0xbe7bbd48,0x3e80,0x3d48be7b,0x3e6d3dc4,0xbe55be0e,0xbdc43e6d,0x3e0ebe55,0x3e353e35,0xbe0ebe55,0xbe353e35,0x3e55be0e,
0x3dc43e6d,0xbd48be7b,0xbe6d3dc4,0x3e7bbd48,0x3e80,0x3e0ebe55,0x3e800000,0xbe55be0e,0xbe6d3dc4,0x3e7b3d48,0x3dc43e6d,0x3d48be7b,
0xbe35be35,0x3d483e7b,0xbe353e35,0x3e7bbd48,0x3dc4be6d,0xbe553e0e,0xbe6dbdc4,0x3e0e3e55,0x3e800000,0xbe55be0e,0xbe80,0xbe0e3e55,
0x3dc43e6d,0x3d48be7b,0x3e6dbdc4,0xbe7bbd48,0xbe353e35,0x3e7bbd48,0x3e353e35,0xbd48be7b,0xbe6dbdc4,0x3e0e3e55,0xbdc43e6d,0x3e55be0e,
0x3e80,0x3e55be0e,0xbe800000,0x3e0e3e55,0xbe6dbdc4,0x3d483e7b,0x3dc4be6d,0xbe7b3d48,0x3e35be35,0xbe7bbd48,0x3e353e35,0x3d48be7b,
0x3dc43e6d,0x3e0ebe55,0xbe6d3dc4,0x3e553e0e,0x3e800000,0xbe0ebe55,0x3e80,0x3e55be0e,0xbdc43e6d,0x3e7bbd48,0xbe6dbdc4,0x3d483e7b,
0xbe35be35,0xbd483e7b,0x3e35be35,0xbe7bbd48,0x3e6dbdc4,0xbe55be0e,0x3dc43e6d,0x3e0ebe55,0x3e80,0x3e7bbd48,0x3e800000,0xbd48be7b,
0xbdc4be6d,0xbe553e0e,0xbe6d3dc4,0x3e0e3e55,0x3e353e35,0x3e0ebe55,0x3e35be35,0xbe55be0e,0xbe6dbdc4,0xbd483e7b,0xbdc43e6d,0x3e7b3d48,
0x3e800000,0xbd48be7b,0xbe80,0xbe7b3d48,0xbe6d3dc4,0x3e0e3e55,0x3dc43e6d,0x3e55be0e,0x3e35be35,0xbe55be0e,0xbe35be35,0xbe0e3e55,
0xbdc43e6d,0x3e7b3d48,0x3e6d3dc4,0x3d48be7b,0x3e80,0x3e7b3d48,0xbe800000,0xbd483e7b,0x3dc4be6d,0xbe55be0e,0x3e6d3dc4,0x3e0ebe55,
0xbe353e35,0x3e0e3e55,0xbe35be35,0xbe553e0e,0x3e6dbdc4,0xbd48be7b,0x3dc43e6d,0x3e7bbd48,0x3e800000,0x3d48be7b,0x3e80,0x3e7b3d48,
0xbe6dbdc4,0xbe0e3e55,0x3dc4be6d,0xbe55be0e,0x3e353e35,0x3e55be0e,0xbe353e35,0x3e0e3e55,0xbdc4be6d,0xbe7b3d48,0x3e6dbdc4,0xbd48be7b,
0x3e80,0x3e553e0e,0x3e800000,0x3e0ebe55,0x3e6dbdc4,0x3d48be7b,0xbdc4be6d,0xbe7bbd48,0xbe35be35,0xbe7b3d48,0xbe353e35,0x3d483e7b,
0xbdc43e6d,0x3e0e3e55,0x3e6d3dc4,0x3e55be0e,0x3e800000,0x3e0ebe55,0xbe80,0xbe55be0e,0xbdc4be6d,0xbe7bbd48,0xbe6d3dc4,0xbd483e7b,
0xbe353e35,0x3d483e7b,0x3e353e35,0x3e7bbd48,0x3e6d3dc4,0x3e55be0e,0x3dc4be6d,0xbe0ebe55,0x3e80,0x3e0e3e55,0xbe800000,0xbe553e0e,
0x3e6d3dc4,0x3e7bbd48,0xbdc43e6d,0x3d483e7b,0x3e35be35,0x3d48be7b,0x3e353e35,0x3e7b3d48,0xbdc4be6d,0xbe55be0e,0x3e6dbdc4,0x3e0ebe55,
0x3e800000,0x3e55be0e,0x3e80,0x3e0e3e55,0x3dc4be6d,0xbd48be7b,0x3e6d3dc4,0x3e7bbd48,0xbe35be35,0xbe7bbd48,0x3e35be35,0x3d48be7b,
0xbe6d3dc4,0xbe0e3e55,0xbdc4be6d,0xbe55be0e,0x3e80,0x3d483e7b,0x3e800000,0x3e7bbd48,0x3dc43e6d,0x3e0e3e55,0x3e6dbdc4,0x3e55be0e,
0x3e353e35,0x3e553e0e,0x3e35be35,0x3e0ebe55,0x3e6d3dc4,0x3e7b3d48,0x3dc4be6d,0x3d48be7b,0x3e800000,0x3e7bbd48,0xbe80,0xbd48be7b,
0x3e6dbdc4,0x3e55be0e,0xbdc4be6d,0xbe0ebe55,0x3e35be35,0x3e0ebe55,0xbe35be35,0xbe55be0e,0x3dc4be6d,0x3d48be7b,0xbe6dbdc4,0xbe7bbd48,
0x3400,0x3364ae1f,0x3400,0x3364ae1f,0x3400,0xb3642e1f,0x3400,0xb3642e1f,0x3400,0x3364ae1f,0x3400,0x3364ae1f,
0x3400,0xb3642e1f,0x3400,0xb3642e1f,0x2bc633c3,0x326db0c4,0x33c3abc6,0xb0c4b26d,0x30c4326d,0xb01d32dd,0x326db0c4,0x32dd301d,
0x32dd301d,0x28b2b3ea,0x301db2dd,0xb3eaa8b2,0x33ea28b2,0x2bc633c3,0x28b2b3ea,0x33c3abc6,0x2f8b330e,0x3113b22f,0xaf8bb30e,0xb113322f,
0x33a82ca5,0x264633f6,0xb3a8aca5,0xa646b3f6,0x330eaf8b,0xb22fb113,0xb30e2f8b,0x322f3113,0x2ca5b3a8,0x33f6a646,0xaca533a8,0xb3f62646,
0x315f31ed,0x2ed7b33b,0xb1ed315f,0x333b2ed7,0x3388ad64,0x315f31ed,0x2d643388,0xb1ed315f,0x2248b3fe,0xb3882d64,0x33fe2248,0xad64b388,
0xb33baed7,0x2248b3fe,0x2ed7b33b,0x33fe2248,0x32a73072,0x2a3eb3d9,0x32a73072,0x2a3eb3d9,0x3072b2a7,0x33d92a3e,0x3072b2a7,0x33d92a3e,
0xb2a7b072,0xaa3e33d9,0xb2a7b072,0xaa3e33d9,0xb07232a7,0xb3d9aa3e,0xb07232a7,0xb3d9aa3e,0x33882d64,0xa248b3fe,0x2d64b388,0xb3fe2248,
0xa248b3fe,0x333baed7,0xb3fe2248,0xaed7b33b,0xb33b2ed7,0x31ed315f,0x2ed7333b,0x315fb1ed,0x31ed315f,0xad643388,0x315fb1ed,0x33882d64,
0x33f62646,0xaca5b3a8,0xb3f6a646,0x2ca533a8,0xb113b22f,0x2f8bb30e,0x3113322f,0xaf8b330e,0xa64633f6,0x33a8aca5,0x2646b3f6,0xb3a82ca5,
0x322fb113,0x330e2f8b,0xb22f3113,0xb30eaf8b,0x33eaa8b2,0xb01db2dd,0x28b233ea,0x32ddb01d,0xb3c3abc6,0xa8b2b3ea,0x2bc6b3c3,0x33eaa8b2,
0x326d30c4,0x2bc6b3c3,0xb0c4326d,0x33c32bc6,0xb01db2dd,0x30c4b26d,0x32ddb01d,0x326d30c4,0x3400,0x3364ae1f,0x3400,0x3364ae1f,
0x3400,0xb3642e1f,0x3400,0xb3642e1f,0x3400,0x3364ae1f,0x3400,0x3364ae1f,0x3400,0xb3642e1f,0x3400,0xb3642e1f,
0xabc6b3c3,0xb26d30c4,0xb3c32bc6,0x30c4326d,0xb0c4b26d,0x301db2dd,0xb26d30c4,0xb2ddb01d,0xb2ddb01d,0xa8b233ea,0xb01d32dd,0x33ea28b2,
0xb3eaa8b2,0xabc6b3c3,0xa8b233ea,0xb3c32bc6,0x2f8b330e,0x3113b22f,0xaf8bb30e,0xb113322f,0x33a82ca5,0x264633f6,0xb3a8aca5,0xa646b3f6,
0x330eaf8b,0xb22fb113,0xb30e2f8b,0x322f3113,0x2ca5b3a8,0x33f6a646,0xaca533a8,0xb3f62646,0xb15fb1ed,0xaed7333b,0x31edb15f,0xb33baed7,
0xb3882d64,0xb15fb1ed,0xad64b388,0x31edb15f,0xa24833fe,0x3388ad64,0xb3fea248,0x2d643388,0x333b2ed7,0xa24833fe,0xaed7333b,0xb3fea248,
0x32a73072,0x2a3eb3d9,0x32a73072,0x2a3eb3d9,0x3072b2a7,0x33d92a3e,0x3072b2a7,0x33d92a3e,0xb2a7b072,0xaa3e33d9,0xb2a7b072,0xaa3e33d9,
0xb07232a7,0xb3d9aa3e,0xb07232a7,0xb3d9aa3e,0xb388ad64,0x224833fe,0xad643388,0x33fea248,0x224833fe,0xb33b2ed7,0x33fea248,0x2ed7333b,
0x333baed7,0xb1edb15f,0xaed7b33b,0xb15f31ed,0xb1edb15f,0x2d64b388,0xb15f31ed,0xb388ad64,0x33f62646,0xaca5b3a8,0xb3f6a646,0x2ca533a8,
0xb113b22f,0x2f8bb30e,0x3113322f,0xaf8b330e,0xa64633f6,0x33a8aca5,0x2646b3f6,0xb3a82ca5,0x322fb113,0x330e2f8b,0xb22f3113,0xb30eaf8b,
0xb3ea28b2,0x301d32dd,0xa8b2b3ea,0xb2dd301d,0x33c32bc6,0x28b233ea,0xabc633c3,0xb3ea28b2,0xb26db0c4,0xabc633c3,0x30c4b26d,0xb3c3abc6,
0x301d32dd,0xb0c4326d,0xb2dd301d,0xb26db0c4,0x34000000,0xae1fb364,0x34000000,0xae1fb364,0x34000000,0x2e1f3364,0x34000000,0x2e1f3364,
0x34000000,0xae1fb364,0x34000000,0xae1fb364,0x34000000,0x2e1f3364,0x34000000,0x2e1f3364,0x33c3abc6,0xb0c4b26d,0xabc6b3c3,0xb26d30c4,
0x326db0c4,0x32dd301d,0xb0c4b26d,0x301db2dd,0x301db2dd,0xb3eaa8b2,0xb2ddb01d,0xa8b233ea,0x28b2b3ea,0x33c3abc6,0xb3eaa8b2,0xabc6b3c3,
0x330eaf8b,0xb22fb113,0xb30e2f8b,0x322f3113,0x2ca5b3a8,0x33f6a646,0xaca533a8,0xb3f62646,0xaf8bb30e,0xb113322f,0x2f8b330e,0x3113b22f,
0xb3a8aca5,0xa646b3f6,0x33a82ca5,0x264633f6,0x31edb15f,0xb33baed7,0x315f31ed,0x2ed7b33b,0xad64b388,0x31edb15f,0x3388ad64,0x315f31ed,
0xb3fea248,0x2d643388,0x2248b3fe,0xb3882d64,0xaed7333b,0xb3fea248,0xb33baed7,0x2248b3fe,0x3072b2a7,0xb3d9aa3e,0x3072b2a7,0xb3d9aa3e,
0xb2a7b072,0x2a3eb3d9,0xb2a7b072,0x2a3eb3d9,0xb07232a7,0x33d92a3e,0xb07232a7,0x33d92a3e,0x32a73072,0xaa3e33d9,0x32a73072,0xaa3e33d9,
0x2d64b388,0xb3fe2248,0xb388ad64,0x224833fe,0xb3fe2248,0xaed7b33b,0x224833fe,0xb33b2ed7,0x2ed7333b,0x315fb1ed,0x333baed7,0xb1edb15f,
0x315fb1ed,0x33882d64,0xb1edb15f,0x2d64b388,0x2646b3f6,0xb3a82ca5,0xa64633f6,0x33a8aca5,0xb22f3113,0xb30eaf8b,0x322fb113,0x330e2f8b,
0x33f62646,0xaca5b3a8,0xb3f6a646,0x2ca533a8,0xb113b22f,0x2f8bb30e,0x3113322f,0xaf8b330e,0xa8b2b3ea,0xb2dd301d,0x33eaa8b2,0xb01db2dd,
0xabc633c3,0xb3ea28b2,0xb3c3abc6,0xa8b2b3ea,0x30c4b26d,0xb3c3abc6,0x326d30c4,0x2bc6b3c3,0xb2dd301d,0xb26db0c4,0xb01db2dd,0x30c4b26d,
0x34000000,0xae1fb364,0x34000000,0xae1fb364,0x34000000,0x2e1f3364,0x34000000,0x2e1f3364,0x34000000,0xae1fb364,0x34000000,0xae1fb364,
0x34000000,0x2e1f3364,0x34000000,0x2e1f3364,0xb3c32bc6,0x30c4326d,0x2bc633c3,0x326db0c4,0xb26d30c4,0xb2ddb01d,0x30c4326d,0xb01d32dd,
0xb01d32dd,0x33ea28b2,0x32dd301d,0x28b2b3ea,0xa8b233ea,0xb3c32bc6,0x33ea28b2,0x2bc633c3,0x330eaf8b,0xb22fb113,0xb30e2f8b,0x322f3113,
0x2ca5b3a8,0x33f6a646,0xaca533a8,0xb3f62646,0xaf8bb30e,0xb113322f,0x2f8b330e,0x3113b22f,0xb3a8aca5,0xa646b3f6,0x33a82ca5,0x264633f6,
0xb1ed315f,0x333b2ed7,0xb15fb1ed,0xaed7333b,0x2d643388,0xb1ed315f,0xb3882d64,0xb15fb1ed,0x33fe2248,0xad64b388,0xa24833fe,0x3388ad64,
0x2ed7b33b,0x33fe2248,0x333b2ed7,0xa24833fe,0x3072b2a7,0xb3d9aa3e,0x3072b2a7,0xb3d9aa3e,0xb2a7b072,0x2a3eb3d9,0xb2a7b072,0x2a3eb3d9,
0xb07232a7,0x33d92a3e,0xb07232a7,0x33d92a3e,0x32a73072,0xaa3e33d9,0x32a73072,0xaa3e33d9,0xad643388,0x33fea248,0x33882d64,0xa248b3fe,
0x33fea248,0x2ed7333b,0xa248b3fe,0x333baed7,0xaed7b33b,0xb15f31ed,0xb33b2ed7,0x31ed315f,0xb15f31ed,0xb388ad64,0x31ed315f,0xad643388,
0x2646b3f6,0xb3a82ca5,0xa64633f6,0x33a8aca5,0xb22f3113,0xb30eaf8b,0x322fb113,0x330e2f8b,0x33f62646,0xaca5b3a8,0xb3f6a646,0x2ca533a8,
0xb113b22f,0x2f8bb30e,0x3113322f,0xaf8b330e,0x28b233ea,0x32ddb01d,0xb3ea28b2,0x301d32dd,0x2bc6b3c3,0x33eaa8b2,0x33c32bc6,0x28b233ea,
0xb0c4326d,0x33c32bc6,0xb26db0c4,0xabc633c3,0x32ddb01d,0x326d30c4,0x301d32dd,0xb0c4326d,0x3e80,0xbd793e78,0xbe6dbdc4,0xbe4ebe18,
0xbdf13e62,0xbe2c3e3e,0xbe22be46,0xbddbbe67,0xbe553e0e,0xbe713dac,0xbd48be7b,0x3c49be80,0xbe7f3cc9,0xbe7dbd16,0x3d95be75,0x3e04be5c,
0x3e800000,0x3e783d79,0xbdc43e6d,0xbe183e4e,0x3e623df1,0x3e3e3e2c,0xbe463e22,0xbe673ddb,0x3e0e3e55,0x3dac3e71,0xbe7b3d48,0xbe80bc49,
0x3cc93e7f,0xbd163e7d,0xbe75bd95,0xbe5cbe04,0x3e80,0xbe183e4e,0x3e6d3dc4,0x3e043e5c,0xbe753d95,0xbe71bdac,0xbcc93e7f,0xbe2c3e3e,
0xbe0ebe55,0x3c49be80,0xbe7b3d48,0xbe67bddb,0x3e22be46,0x3e78bd79,0xbdf1be62,0x3d16be7d,0x3e800000,0x3e4e3e18,0x3dc4be6d,0x3e5cbe04,
0x3d953e75,0xbdac3e71,0x3e7f3cc9,0x3e3e3e2c,0xbe553e0e,0xbe80bc49,0x3d483e7b,0xbddb3e67,0xbe46be22,0xbd79be78,0xbe623df1,0xbe7dbd16,
0x3e80,0xbe5c3e04,0xbe6dbdc4,0xbd16be7d,0xbe62bdf1,0xbc49be80,0x3e46be22,0x3e713dac,0x3e55be0e,0x3e673ddb,0x3d483e7b,0xbe3e3e2c,
0x3cc93e7f,0xbe4e3e18,0xbe75bd95,0xbd79be78,0x3e800000,0x3e043e5c,0xbdc43e6d,0xbe7d3d16,0xbdf13e62,0xbe803c49,0xbe22be46,0x3dacbe71,
0xbe0ebe55,0x3ddbbe67,0x3e7bbd48,0x3e2c3e3e,0x3e7fbcc9,0x3e183e4e,0xbd953e75,0xbe783d79,0x3e80,0xbe7d3d16,0x3e6d3dc4,0xbd793e78,
0xbd95be75,0x3e67bddb,0xbe7fbcc9,0xbc49be80,0x3e0e3e55,0xbe3e3e2c,0x3e7bbd48,0x3dac3e71,0xbe46be22,0x3e04be5c,0xbe623df1,0xbe18be4e,
0x3e800000,0x3d163e7d,0x3dc4be6d,0x3e783d79,0xbe753d95,0xbddbbe67,0xbcc93e7f,0xbe803c49,0x3e55be0e,0x3e2c3e3e,0xbd48be7b,0x3e71bdac,
0xbe223e46,0xbe5cbe04,0x3df13e62,0xbe4e3e18,0x3e80,0xbe78bd79,0xbe6dbdc4,0x3e18be4e,0x3df1be62,0x3e3e3e2c,0x3e223e46,0xbe673ddb,
0xbe553e0e,0xbdacbe71,0xbd48be7b,0x3e803c49,0x3e7fbcc9,0xbd163e7d,0xbd953e75,0xbe5cbe04,0x3e800000,0xbd793e78,0xbdc43e6d,0xbe4ebe18,
0xbe62bdf1,0x3e2cbe3e,0x3e46be22,0x3ddb3e67,0x3e0e3e55,0xbe713dac,0xbe7b3d48,0x3c49be80,0xbcc9be7f,0x3e7d3d16,0x3e753d95,0xbe043e5c,
0x3e80,0xbe4ebe18,0x3e6d3dc4,0xbe5c3e04,0x3e75bd95,0xbdac3e71,0x3cc9be7f,0x3e3e3e2c,0xbe0ebe55,0x3e803c49,0xbe7b3d48,0x3ddbbe67,
0xbe223e46,0xbd79be78,0x3df13e62,0xbe7dbd16,0x3e800000,0xbe183e4e,0x3dc4be6d,0x3e043e5c,0xbd95be75,0x3e713dac,0xbe7fbcc9,0x3e2cbe3e,
0xbe553e0e,0x3c49be80,0x3d483e7b,0xbe67bddb,0x3e463e22,0xbe783d79,0x3e62bdf1,0xbd163e7d,0x3e80,0xbe04be5c,0xbe6dbdc4,0x3e7dbd16,
0x3e623df1,0xbe803c49,0xbe463e22,0x3dacbe71,0x3e55be0e,0xbddb3e67,0x3d483e7b,0xbe2cbe3e,0xbcc9be7f,0x3e183e4e,0x3e753d95,0xbe783d79,
0x3e800000,0xbe5c3e04,0xbdc43e6d,0xbd16be7d,0x3df1be62,0x3c493e80,0x3e223e46,0xbe71bdac,0xbe0ebe55,0x3e673ddb,0x3e7bbd48,0xbe3e3e2c,
0xbe7f3cc9,0x3e4ebe18,0x3d95be75,0x3d793e78,0x3e80,0xbd16be7d,0x3e6d3dc4,0xbe78bd79,0x3d953e75,0xbddbbe67,0x3e7f3cc9,0xbe803c49,
0x3e0e3e55,0xbe2cbe3e,0x3e7bbd48,0xbe713dac,0x3e463e22,0xbe5cbe04,0x3e62bdf1,0xbe4e3e18,0x3e800000,0xbe7d3d16,0x3dc4be6d,0xbd793e78,
0x3e75bd95,0xbe673ddb,0x3cc9be7f,0x3c493e80,0x3e55be0e,0xbe3e3e2c,0xbd48be7b,0x3dac3e71,0x3e22be46,0xbe043e5c,0xbdf1be62,0x3e183e4e,
0x3e80,0x3d79be78,0xbe6dbdc4,0x3e4e3e18,0xbdf13e62,0x3e2cbe3e,0xbe22be46,0x3ddb3e67,0xbe553e0e,0x3e71bdac,0xbd48be7b,0xbc493e80,
0xbe7f3cc9,0x3e7d3d16,0x3d95be75,0xbe043e5c,0x3e800000,0xbe78bd79,0xbdc43e6d,0x3e18be4e,0x3e623df1,0xbe3ebe2c,0xbe463e22,0x3e67bddb,
0x3e0e3e55,0xbdacbe71,0xbe7b3d48,0x3e803c49,0x3cc93e7f,0x3d16be7d,0xbe75bd95,0x3e5c3e04,0x3e80,0x3e18be4e,0x3e6d3dc4,0xbe04be5c,
0xbe753d95,0x3e713dac,0xbcc93e7f,0x3e2cbe3e,0xbe0ebe55,0xbc493e80,0xbe7b3d48,0x3e673ddb,0x3e22be46,0xbe783d79,0xbdf1be62,0xbd163e7d,
0x3e800000,0xbe4ebe18,0x3dc4be6d,0xbe5c3e04,0x3d953e75,0x3dacbe71,0x3e7f3cc9,0xbe3ebe2c,0xbe553e0e,0x3e803c49,0x3d483e7b,0x3ddbbe67,
0xbe46be22,0x3d793e78,0xbe623df1,0x3e7d3d16,0x3e80,0x3e5cbe04,0xbe6dbdc4,0x3d163e7d,0xbe62bdf1,0x3c493e80,0x3e46be22,0xbe71bdac,
0x3e55be0e,0xbe67bddb,0x3d483e7b,0x3e3ebe2c,0x3cc93e7f,0x3e4ebe18,0xbe75bd95,0x3d793e78,0x3e800000,0xbe04be5c,0xbdc43e6d,0x3e7dbd16,
0xbdf13e62,0x3e80bc49,0xbe22be46,0xbdac3e71,0xbe0ebe55,0xbddb3e67,0x3e7bbd48,0xbe2cbe3e,0x3e7fbcc9,0xbe18be4e,0xbd953e75,0x3e78bd79,
0x3e80,0x3e7dbd16,0x3e6d3dc4,0x3d79be78,0xbd95be75,0xbe673ddb,0xbe7fbcc9,0x3c493e80,0x3e0e3e55,0x3e3ebe2c,0x3e7bbd48,0xbdacbe71,
0xbe46be22,0xbe043e5c,0xbe623df1,0x3e183e4e,0x3e800000,0xbd16be7d,0x3dc4be6d,0xbe78bd79,0xbe753d95,0x3ddb3e67,0xbcc93e7f,0x3e80bc49,
0x3e55be0e,0xbe2cbe3e,0xbd48be7b,0xbe713dac,0xbe223e46,0x3e5c3e04,0x3df13e62,0x3e4ebe18,0x3e80,0x3e783d79,0xbe6dbdc4,0xbe183e4e,
0x3df1be62,0xbe3ebe2c,0x3e223e46,0x3e67bddb,0xbe553e0e,0x3dac3e71,0xbd48be7b,0xbe80bc49,0x3e7fbcc9,0x3d16be7d,0xbd953e75,0x3e5c3e04,
0x3e800000,0x3d79be78,0xbdc43e6d,0x3e4e3e18,0xbe62bdf1,0xbe2c3e3e,0x3e46be22,0xbddbbe67,0x3e0e3e55,0x3e71bdac,0xbe7b3d48,0xbc493e80,
0xbcc9be7f,0xbe7dbd16,0x3e753d95,0x3e04be5c,0x3e80,0x3e4e3e18,0x3e6d3dc4,0x3e5cbe04,0x3e75bd95,0x3dacbe71,0x3cc9be7f,0xbe3ebe2c,
0xbe0ebe55,0xbe80bc49,0xbe7b3d48,0xbddb3e67,0xbe223e46,0x3d793e78,0x3df13e62,0x3e7d3d16,0x3e800000,0x3e18be4e,0x3dc4be6d,0xbe04be5c,
0xbd95be75,0xbe71bdac,0xbe7fbcc9,0xbe2c3e3e,0xbe553e0e,0xbc493e80,0x3d483e7b,0x3e673ddb,0x3e463e22,0x3e78bd79,0x3e62bdf1,0x3d16be7d,
0x3e80,0x3e043e5c,0xbe6dbdc4,0xbe7d3d16,0x3e623df1,0x3e80bc49,0xbe463e22,0xbdac3e71,0x3e55be0e,0x3ddbbe67,0x3d483e7b,0x3e2c3e3e,
0xbcc9be7f,0xbe18be4e,0x3e753d95,0x3e78bd79,0x3e800000,0x3e5cbe04,0xbdc43e6d,0x3d163e7d,0x3df1be62,0xbc49be80,0x3e223e46,0x3e713dac,
0xbe0ebe55,0xbe67bddb,0x3e7bbd48,0x3e3ebe2c,0xbe7f3cc9,0xbe4e3e18,0x3d95be75,0xbd79be78,0x3e80,0x3d163e7d,0x3e6d3dc4,0x3e783d79,
0x3d953e75,0x3ddb3e67,0x3e7f3cc9,0x3e80bc49,0x3e0e3e55,0x3e2c3e3e,0x3e7bbd48,0x3e71bdac,0x3e463e22,0x3e5c3e04,0x3e62bdf1,0x3e4ebe18,
0x3e800000,0x3e7dbd16,0x3dc4be6d,0x3d79be78,0x3e75bd95,0x3e67bddb,0x3cc9be7f,0xbc49be80,0x3e55be0e,0x3e3ebe2c,0xbd48be7b,0xbdacbe71,
0x3e22be46,0x3e04be5c,0xbdf1be62,0xbe18be4e,0x3400,0x31a8b1a8,0x3400,0x31a8b1a8,0x3400,0xb1a831a8,0x3400,0xb1a831a8,
0x3400,0x31a8b1a8,0x3400,0x31a8b1a8,0x3400,0xb1a831a8,0x3400,0xb1a831a8,0x2ca533a8,0x2f8bb30e,0x33a8aca5,0xb30eaf8b,
0x3113322f,0xa64633f6,0x322fb113,0x33f62646,0x330e2f8b,0xaca5b3a8,0x2f8bb30e,0xb3a82ca5,0x33f62646,0x3113322f,0x2646b3f6,0x322fb113,
0x307232a7,0x2a3eb3d9,0xb072b2a7,0xaa3e33d9,0x33d92a3e,0x307232a7,0xb3d9aa3e,0xb072b2a7,0x32a7b072,0xb3d9aa3e,0xb2a73072,0x33d92a3e,
0x2a3eb3d9,0x32a7b072,0xaa3e33d9,0xb2a73072,0x322f3113,0xa646b3f6,0xb113322f,0x33f6a646,0x330eaf8b,0x33a82ca5,0x2f8b330e,0xaca533a8,
0xa646b3f6,0xb113322f,0x33f6a646,0xb22fb113,0xb3a8aca5,0xaf8bb30e,0x2ca5b3a8,0x330eaf8b,0x33642e1f,0xae1fb364,0x33642e1f,0xae1fb364,
0x2e1fb364,0x3364ae1f,0x2e1fb364,0x3364ae1f,0xb364ae1f,0x2e1f3364,0xb364ae1f,0x2e1f3364,0xae1f3364,0xb3642e1f,0xae1f3364,0xb3642e1f,
0x33f62646,0xb113b22f,0x2646b3f6,0xb22f3113,0xaca5b3a8,0x2f8bb30e,0xb3a82ca5,0xb30eaf8b,0xb22f3113,0x33f62646,0x3113322f,0x2646b3f6,
0x330e2f8b,0x2ca533a8,0x2f8bb30e,0x33a8aca5,0x33d9aa3e,0xb2a7b072,0xb3d92a3e,0x32a73072,0xb2a7b072,0xaa3eb3d9,0x32a73072,0x2a3e33d9,
0x2a3e33d9,0x3072b2a7,0xaa3eb3d9,0xb07232a7,0x3072b2a7,0x33d9aa3e,0xb07232a7,0xb3d92a3e,0x330eaf8b,0xb3a8aca5,0x2f8b330e,0x2ca5b3a8,
0xb3f62646,0xb22fb113,0xa646b3f6,0x3113b22f,0x33a82ca5,0xaf8bb30e,0xaca533a8,0x330eaf8b,0xb22fb113,0xa646b3f6,0x3113b22f,0x33f6a646,
0x3400,0x31a8b1a8,0x3400,0x31a8b1a8,0x3400,0xb1a831a8,0x3400,0xb1a831a8,0x3400,0x31a8b1a8,0x3400,0x31a8b1a8,
0x3400,0xb1a831a8,0x3400,0xb1a831a8,0xaca5b3a8,0xaf8b330e,0xb3a82ca5,0x330e2f8b,0xb113b22f,0x2646b3f6,0xb22f3113,0xb3f6a646,
0xb30eaf8b,0x2ca533a8,0xaf8b330e,0x33a8aca5,0xb3f6a646,0xb113b22f,0xa64633f6,0xb22f3113,0x307232a7,0x2a3eb3d9,0xb072b2a7,0xaa3e33d9,
0x33d92a3e,0x307232a7,0xb3d9aa3e,0xb072b2a7,0x32a7b072,0xb3d9aa3e,0xb2a73072,0x33d92a3e,0x2a3eb3d9,0x32a7b072,0xaa3e33d9,0xb2a73072,
0xb22fb113,0x264633f6,0x3113b22f,0xb3f62646,0xb30e2f8b,0xb3a8aca5,0xaf8bb30e,0x2ca5b3a8,0x264633f6,0x3113b22f,0xb3f62646,0x322f3113,
0x33a82ca5,0x2f8b330e,0xaca533a8,0xb30e2f8b,0x33642e1f,0xae1fb364,0x33642e1f,0xae1fb364,0x2e1fb364,0x3364ae1f,0x2e1fb364,0x3364ae1f,
0xb364ae1f,0x2e1f3364,0xb364ae1f,0x2e1f3364,0xae1f3364,0xb3642e1f,0xae1f3364,0xb3642e1f,0xb3f6a646,0x3113322f,0xa64633f6,0x322fb113,
0x2ca533a8,0xaf8b330e,0x33a8aca5,0x330e2f8b,0x322fb113,0xb3f6a646,0xb113b22f,0xa64633f6,0xb30eaf8b,0xaca5b3a8,0xaf8b330e,0xb3a82ca5,
0x33d9aa3e,0xb2a7b072,0xb3d92a3e,0x32a73072,0xb2a7b072,0xaa3eb3d9,0x32a73072,0x2a3e33d9,0x2a3e33d9,0x3072b2a7,0xaa3eb3d9,0xb07232a7,
0x3072b2a7,0x33d9aa3e,0xb07232a7,0xb3d92a3e,0xb30e2f8b,0x33a82ca5,0xaf8bb30e,0xaca533a8,0x33f6a646,0x322f3113,0x264633f6,0xb113322f,
0xb3a8aca5,0x2f8b330e,0x2ca5b3a8,0xb30e2f8b,0x322f3113,0x264633f6,0xb113322f,0xb3f62646,0x34000000,0xb1a8b1a8,0x34000000,0xb1a8b1a8,
0x34000000,0x31a831a8,0x34000000,0x31a831a8,0x34000000,0xb1a8b1a8,0x34000000,0xb1a8b1a8,0x34000000,0x31a831a8,0x34000000,0x31a831a8,
0x33a8aca5,0xb30eaf8b,0xaca5b3a8,0xaf8b330e,0x322fb113,0x33f62646,0xb113b22f,0x2646b3f6,0x2f8bb30e,0xb3a82ca5,0xb30eaf8b,0x2ca533a8,
0x2646b3f6,0x322fb113,0xb3f6a646,0xb113b22f,0x32a7b072,0xb3d9aa3e,0xb2a73072,0x33d92a3e,0x2a3eb3d9,0x32a7b072,0xaa3e33d9,0xb2a73072,
0xb072b2a7,0xaa3e33d9,0x307232a7,0x2a3eb3d9,0xb3d9aa3e,0xb072b2a7,0x33d92a3e,0x307232a7,0x3113b22f,0xb3f62646,0x322f3113,0xa646b3f6,
0xaf8bb30e,0x2ca5b3a8,0x330eaf8b,0x33a82ca5,0xb3f62646,0x322f3113,0xa646b3f6,0xb113322f,0xaca533a8,0xb30e2f8b,0xb3a8aca5,0xaf8bb30e,
0x2e1fb364,0xb3642e1f,0x2e1fb364,0xb3642e1f,0xb364ae1f,0xae1fb364,0xb364ae1f,0xae1fb364,0xae1f3364,0x3364ae1f,0xae1f3364,0x3364ae1f,
0x33642e1f,0x2e1f3364,0x33642e1f,0x2e1f3364,0x2646b3f6,0xb22f3113,0xb3f6a646,0x3113322f,0xb3a82ca5,0xb30eaf8b,0x2ca533a8,0xaf8b330e,
0x3113322f,0x2646b3f6,0x322fb113,0xb3f6a646,0x2f8bb30e,0x33a8aca5,0xb30eaf8b,0xaca5b3a8,0xaa3eb3d9,0xb07232a7,0x2a3e33d9,0x3072b2a7,
0xb07232a7,0xb3d92a3e,0x3072b2a7,0x33d9aa3e,0x33d9aa3e,0xb2a7b072,0xb3d92a3e,0x32a73072,0xb2a7b072,0xaa3eb3d9,0x32a73072,0x2a3e33d9,
0xaf8bb30e,0xaca533a8,0x330eaf8b,0xb3a8aca5,0x264633f6,0xb113322f,0xb3f62646,0xb22fb113,0x2ca5b3a8,0xb30e2f8b,0x33a82ca5,0xaf8bb30e,
0xb113322f,0xb3f62646,0xb22fb113,0xa646b3f6,0x34000000,0xb1a8b1a8,0x34000000,0xb1a8b1a8,0x34000000,0x31a831a8,0x34000000,0x31a831a8,
0x34000000,0xb1a8b1a8,0x34000000,0xb1a8b1a8,0x34000000,0x31a831a8,0x34000000,0x31a831a8,0xb3a82ca5,0x330e2f8b,0x2ca533a8,0x2f8bb30e,
0xb22f3113,0xb3f6a646,0x3113322f,0xa64633f6,0xaf8b330e,0x33a8aca5,0x330e2f8b,0xaca5b3a8,0xa64633f6,0xb22f3113,0x33f62646,0x3113322f,
0x32a7b072,0xb3d9aa3e,0xb2a73072,0x33d92a3e,0x2a3eb3d9,0x32a7b072,0xaa3e33d9,0xb2a73072,0xb072b2a7,0xaa3e33d9,0x307232a7,0x2a3eb3d9,
0xb3d9aa3e,0xb072b2a7,0x33d92a3e,0x307232a7,0xb113322f,0x33f6a646,0xb22fb113,0x264633f6,0x2f8b330e,0xaca533a8,0xb30e2f8b,0xb3a8aca5,
0x33f6a646,0xb22fb113,0x264633f6,0x3113b22f,0x2ca5b3a8,0x330eaf8b,0x33a82ca5,0x2f8b330e,0x2e1fb364,0xb3642e1f,0x2e1fb364,0xb3642e1f,
0xb364ae1f,0xae1fb364,0xb364ae1f,0xae1fb364,0xae1f3364,0x3364ae1f,0xae1f3364,0x3364ae1f,0x33642e1f,0x2e1f3364,0x33642e1f,0x2e1f3364,
0xa64633f6,0x322fb113,0x33f62646,0xb113b22f,0x33a8aca5,0x330e2f8b,0xaca5b3a8,0x2f8bb30e,0xb113b22f,0xa64633f6,0xb22f3113,0x33f62646,
0xaf8b330e,0xb3a82ca5,0x330e2f8b,0x2ca533a8,0xaa3eb3d9,0xb07232a7,0x2a3e33d9,0x3072b2a7,0xb07232a7,0xb3d92a3e,0x3072b2a7,0x33d9aa3e,
0x33d9aa3e,0xb2a7b072,0xb3d92a3e,0x32a73072,0xb2a7b072,0xaa3eb3d9,0x32a73072,0x2a3e33d9,0x2f8b330e,0x2ca5b3a8,0xb30e2f8b,0x33a82ca5,
0xa646b3f6,0x3113b22f,0x33f6a646,0x322f3113,0xaca533a8,0x330eaf8b,0xb3a8aca5,0x2f8b330e,0x3113b22f,0x33f6a646,0x322f3113,0x264633f6,
0x3e80,0xbd953e75,0xbe35be35,0xbdf1be62,0xbe0e3e55,0xbe463e22,0xbd48be7b,0x3cc9be7f,0xbe6d3dc4,0xbe7f3cc9,0x3dc4be6d,0x3e22be46,
0xbe7bbd48,0xbe62bdf1,0x3e55be0e,0x3e75bd95,0x3e800000,0x3e753d95,0xbe353e35,0xbe623df1,0x3e553e0e,0x3e223e46,0xbe7b3d48,0xbe7fbcc9,
0x3dc43e6d,0x3cc93e7f,0xbe6dbdc4,0xbe46be22,0xbd483e7b,0xbdf13e62,0xbe0ebe55,0xbd95be75,0x3e80,0xbe223e46,0x3e353e35,0x3cc93e7f,
0xbe7b3d48,0xbe62bdf1,0xbe0e3e55,0xbe753d95,0xbdc4be6d,0x3d95be75,0xbe6dbdc4,0xbdf1be62,0x3e55be0e,0x3e7f3cc9,0x3d48be7b,0x3e46be22,
0x3e800000,0x3e463e22,0x3e35be35,0x3e7fbcc9,0x3d483e7b,0xbdf13e62,0x3e553e0e,0x3d953e75,0xbe6d3dc4,0xbe75bd95,0xbdc43e6d,0xbe623df1,
0xbe0ebe55,0x3cc9be7f,0xbe7bbd48,0xbe22be46,0x3e80,0xbe623df1,0xbe35be35,0x3d95be75,0xbe55be0e,0x3cc9be7f,0x3e7bbd48,0x3e223e46,
0x3e6dbdc4,0x3e463e22,0xbdc43e6d,0xbe7f3cc9,0xbd483e7b,0xbe753d95,0xbe0ebe55,0x3df1be62,0x3e800000,0x3df13e62,0xbe353e35,0xbe75bd95,
0xbe0e3e55,0xbe7fbcc9,0xbd48be7b,0x3e46be22,0xbdc4be6d,0x3e22be46,0x3e6d3dc4,0x3cc93e7f,0x3e7b3d48,0x3d953e75,0xbe553e0e,0xbe62bdf1,
0x3e80,0xbe7f3cc9,0x3e353e35,0xbe223e46,0xbd48be7b,0x3e75bd95,0xbe55be0e,0x3df1be62,0x3dc43e6d,0xbe623df1,0x3e6d3dc4,0xbd953e75,
0xbe0ebe55,0x3e46be22,0xbe7bbd48,0x3cc9be7f,0x3e800000,0x3cc93e7f,0x3e35be35,0x3e463e22,0xbe7b3d48,0xbd95be75,0xbe0e3e55,0xbe62bdf1,
0x3e6dbdc4,0x3df13e62,0x3dc4be6d,0x3e753d95,0xbe553e0e,0xbe22be46,0xbd483e7b,0xbe7fbcc9,0x3e80,0xbe75bd95,0xbe35be35,0x3e62bdf1,
0x3e0ebe55,0x3e223e46,0x3d483e7b,0xbe7fbcc9,0xbe6d3dc4,0xbcc9be7f,0x3dc4be6d,0x3e463e22,0x3e7b3d48,0xbdf13e62,0xbe553e0e,0xbd95be75,
0x3e800000,0xbd953e75,0xbe353e35,0xbdf1be62,0xbe55be0e,0x3e46be22,0x3e7bbd48,0xbcc93e7f,0x3dc43e6d,0xbe7f3cc9,0xbe6dbdc4,0x3e22be46,
0x3d48be7b,0x3e623df1,0x3e0e3e55,0xbe753d95,0x3e80,0xbe46be22,0x3e353e35,0xbe7f3cc9,0x3e7bbd48,0xbdf13e62,0x3e0ebe55,0x3d953e75,
0xbdc4be6d,0x3e753d95,0xbe6dbdc4,0x3e62bdf1,0xbe553e0e,0x3cc9be7f,0xbd483e7b,0xbe22be46,0x3e800000,0xbe223e46,0x3e35be35,0x3cc93e7f,
0xbd48be7b,0x3e623df1,0xbe55be0e,0x3e75bd95,0xbe6d3dc4,0x3d95be75,0xbdc43e6d,0xbdf1be62,0x3e0e3e55,0xbe7fbcc9,0x3e7b3d48,0xbe463e22,
0x3e80,0xbdf1be62,0xbe35be35,0x3e753d95,0x3e553e0e,0xbe7fbcc9,0xbe7b3d48,0x3e46be22,0x3e6dbdc4,0xbe223e46,0xbdc43e6d,0xbcc9be7f,
0x3d48be7b,0x3d953e75,0x3e0e3e55,0xbe62bdf1,0x3e800000,0xbe623df1,0xbe353e35,0x3d95be75,0x3e0ebe55,0xbcc93e7f,0x3d483e7b,0xbe22be46,
0xbdc4be6d,0x3e463e22,0x3e6d3dc4,0xbe7f3cc9,0xbe7bbd48,0x3e75bd95,0x3e55be0e,0xbdf13e62,0x3e80,0xbcc9be7f,0x3e353e35,0xbe46be22,
0x3d483e7b,0xbd95be75,0x3e553e0e,0xbe62bdf1,0x3dc43e6d,0xbdf1be62,0x3e6d3dc4,0xbe75bd95,0x3e0e3e55,0xbe22be46,0x3e7b3d48,0xbe7fbcc9,
0x3e800000,0xbe7f3cc9,0x3e35be35,0xbe223e46,0x3e7bbd48,0xbe753d95,0x3e0ebe55,0xbdf13e62,0x3e6dbdc4,0xbe623df1,0x3dc4be6d,0xbd953e75,
0x3e55be0e,0xbe463e22,0x3d48be7b,0xbcc93e7f,0x3e80,0x3d95be75,0xbe35be35,0x3df13e62,0xbe0e3e55,0x3e46be22,0xbd48be7b,0xbcc93e7f,
0xbe6d3dc4,0x3e7fbcc9,0x3dc4be6d,0xbe223e46,0xbe7bbd48,0x3e623df1,0x3e55be0e,0xbe753d95,0x3e800000,0xbe75bd95,0xbe353e35,0x3e62bdf1,
0x3e553e0e,0xbe22be46,0xbe7b3d48,0x3e7f3cc9,0x3dc43e6d,0xbcc9be7f,0xbe6dbdc4,0x3e463e22,0xbd483e7b,0x3df1be62,0xbe0ebe55,0x3d953e75,
0x3e80,0x3e22be46,0x3e353e35,0xbcc9be7f,0xbe7b3d48,0x3e623df1,0xbe0e3e55,0x3e75bd95,0xbdc4be6d,0xbd953e75,0xbe6dbdc4,0x3df13e62,
0x3e55be0e,0xbe7fbcc9,0x3d48be7b,0xbe463e22,0x3e800000,0xbe46be22,0x3e35be35,0xbe7f3cc9,0x3d483e7b,0x3df1be62,0x3e553e0e,0xbd95be75,
0xbe6d3dc4,0x3e753d95,0xbdc43e6d,0x3e62bdf1,0xbe0ebe55,0xbcc93e7f,0xbe7bbd48,0x3e223e46,0x3e80,0x3e62bdf1,0xbe35be35,0xbd953e75,
0xbe55be0e,0xbcc93e7f,0x3e7bbd48,0xbe22be46,0x3e6dbdc4,0xbe46be22,0xbdc43e6d,0x3e7fbcc9,0xbd483e7b,0x3e75bd95,0xbe0ebe55,0xbdf13e62,
0x3e800000,0xbdf1be62,0xbe353e35,0x3e753d95,0xbe0e3e55,0x3e7f3cc9,0xbd48be7b,0xbe463e22,0xbdc4be6d,0xbe223e46,0x3e6d3dc4,0xbcc9be7f,
0x3e7b3d48,0xbd95be75,0xbe553e0e,0x3e623df1,0x3e80,0x3e7fbcc9,0x3e353e35,0x3e22be46,0xbd48be7b,0xbe753d95,0xbe55be0e,0xbdf13e62,
0x3dc43e6d,0x3e62bdf1,0x3e6d3dc4,0x3d95be75,0xbe0ebe55,0xbe463e22,0xbe7bbd48,0xbcc93e7f,0x3e800000,0xbcc9be7f,0x3e35be35,0xbe46be22,
0xbe7b3d48,0x3d953e75,0xbe0e3e55,0x3e623df1,0x3e6dbdc4,0xbdf1be62,0x3dc4be6d,0xbe75bd95,0xbe553e0e,0x3e223e46,0xbd483e7b,0x3e7f3cc9,
0x3e80,0x3e753d95,0xbe35be35,0xbe623df1,0x3e0ebe55,0xbe22be46,0x3d483e7b,0x3e7f3cc9,0xbe6d3dc4,0x3cc93e7f,0x3dc4be6d,0xbe46be22,
0x3e7b3d48,0x3df1be62,0xbe553e0e,0x3d953e75,0x3e800000,0x3d95be75,0xbe353e35,0x3df13e62,0xbe55be0e,0xbe463e22,0x3e7bbd48,0x3cc9be7f,
0x3dc43e6d,0x3e7fbcc9,0xbe6dbdc4,0xbe223e46,0x3d48be7b,0xbe62bdf1,0x3e0e3e55,0x3e75bd95,0x3e80,0x3e463e22,0x3e353e35,0x3e7fbcc9,
0x3e7bbd48,0x3df1be62,0x3e0ebe55,0xbd95be75,0xbdc4be6d,0xbe75bd95,0xbe6dbdc4,0xbe623df1,0xbe553e0e,0xbcc93e7f,0xbd483e7b,0x3e223e46,
0x3e800000,0x3e22be46,0x3e35be35,0xbcc9be7f,0xbd48be7b,0xbe62bdf1,0xbe55be0e,0xbe753d95,0xbe6d3dc4,0xbd953e75,0xbdc43e6d,0x3df13e62,
0x3e0e3e55,0x3e7f3cc9,0x3e7b3d48,0x3e46be22,0x3e80,0x3df13e62,0xbe35be35,0xbe75bd95,0x3e553e0e,0x3e7f3cc9,0xbe7b3d48,0xbe463e22,
0x3e6dbdc4,0x3e22be46,0xbdc43e6d,0x3cc93e7f,0x3d48be7b,0xbd95be75,0x3e0e3e55,0x3e623df1,0x3e800000,0x3e62bdf1,0xbe353e35,0xbd953e75,
0x3e0ebe55,0x3cc9be7f,0x3d483e7b,0x3e223e46,0xbdc4be6d,0xbe46be22,0x3e6d3dc4,0x3e7fbcc9,0xbe7bbd48,0xbe753d95,0x3e55be0e,0x3df1be62,
0x3e80,0x3cc93e7f,0x3e353e35,0x3e463e22,0x3d483e7b,0x3d953e75,0x3e553e0e,0x3e623df1,0x3dc43e6d,0x3df13e62,0x3e6d3dc4,0x3e753d95,
0x3e0e3e55,0x3e223e46,0x3e7b3d48,0x3e7f3cc9,0x3e800000,0x3e7fbcc9,0x3e35be35,0x3e22be46,0x3e7bbd48,0x3e75bd95,0x3e0ebe55,0x3df1be62,
0x3e6dbdc4,0x3e62bdf1,0x3dc4be6d,0x3d95be75,0x3e55be0e,0x3e46be22,0x3d48be7b,0x3cc9be7f,0x3400,0x2e1fb364,0x3400,0x2e1fb364,
0x3400,0xae1f3364,0x3400,0xae1f3364,0x3400,0x2e1fb364,0x3400,0x2e1fb364,0x3400,0xae1f3364,0x3400,0xae1f3364,
0x2d643388,0x2248b3fe,0x3388ad64,0xb3fea248,0x315f31ed,0x2d643388,0x31edb15f,0x3388ad64,0x333b2ed7,0xb15fb1ed,0x2ed7b33b,0xb1ed315f,
0x33fe2248,0x333b2ed7,0x2248b3fe,0x2ed7b33b,0x3113322f,0xaca5b3a8,0xb113b22f,0x2ca533a8,0x33f62646,0x330e2f8b,0xb3f6a646,0xb30eaf8b,
0x322fb113,0xb3a82ca5,0xb22f3113,0x33a8aca5,0x2646b3f6,0x2f8bb30e,0xa64633f6,0xaf8b330e,0x32dd301d,0xb0c4b26d,0xb01d32dd,0x326db0c4,
0x326db0c4,0x33c3abc6,0x30c4326d,0x2bc633c3,0xabc6b3c3,0xa8b233ea,0x33c3abc6,0xb3eaa8b2,0xb3eaa8b2,0xb2ddb01d,0x28b2b3ea,0x301db2dd,
0x33d92a3e,0xb2a7b072,0x33d92a3e,0xb2a7b072,0x2a3eb3d9,0x3072b2a7,0x2a3eb3d9,0x3072b2a7,0xb3d9aa3e,0x32a73072,0xb3d9aa3e,0x32a73072,
0xaa3e33d9,0xb07232a7,0xaa3e33d9,0xb07232a7,0x33eaa8b2,0xb3c3abc6,0xa8b2b3ea,0xabc633c3,0xb01db2dd,0xa8b2b3ea,0xb2dd301d,0xb3ea28b2,
0xb0c4326d,0x32ddb01d,0x326d30c4,0xb01db2dd,0x33c32bc6,0x326d30c4,0x2bc6b3c3,0x30c4b26d,0x330eaf8b,0xb3f62646,0xb30e2f8b,0x33f6a646,
0xb3a8aca5,0xb22fb113,0x33a82ca5,0x322f3113,0x2f8b330e,0xa646b3f6,0xaf8bb30e,0x264633f6,0x2ca5b3a8,0x3113b22f,0xaca533a8,0xb113322f,
0x315fb1ed,0xb33b2ed7,0x31ed315f,0xaed7b33b,0xb33b2ed7,0xb3fe2248,0xaed7b33b,0xa248b3fe,0x33fea248,0xb388ad64,0x224833fe,0x2d64b388,
0xb388ad64,0xb1edb15f,0x2d64b388,0x315fb1ed,0x3400,0x2e1fb364,0x3400,0x2e1fb364,0x3400,0xae1f3364,0x3400,0xae1f3364,
0x3400,0x2e1fb364,0x3400,0x2e1fb364,0x3400,0xae1f3364,0x3400,0xae1f3364,0xad64b388,0xa24833fe,0xb3882d64,0x33fe2248,
0xb15fb1ed,0xad64b388,0xb1ed315f,0xb3882d64,0xb33baed7,0x315f31ed,0xaed7333b,0x31edb15f,0xb3fea248,0xb33baed7,0xa24833fe,0xaed7333b,
0x3113322f,0xaca5b3a8,0xb113b22f,0x2ca533a8,0x33f62646,0x330e2f8b,0xb3f6a646,0xb30eaf8b,0x322fb113,0xb3a82ca5,0xb22f3113,0x33a8aca5,
0x2646b3f6,0x2f8bb30e,0xa64633f6,0xaf8b330e,0xb2ddb01d,0x30c4326d,0x301db2dd,0xb26d30c4,0xb26d30c4,0xb3c32bc6,0xb0c4b26d,0xabc6b3c3,
0x2bc633c3,0x28b2b3ea,0xb3c32bc6,0x33ea28b2,0x33ea28b2,0x32dd301d,0xa8b233ea,0xb01d32dd,0x33d92a3e,0xb2a7b072,0x33d92a3e,0xb2a7b072,
0x2a3eb3d9,0x3072b2a7,0x2a3eb3d9,0x3072b2a7,0xb3d9aa3e,0x32a73072,0xb3d9aa3e,0x32a73072,0xaa3e33d9,0xb07232a7,0xaa3e33d9,0xb07232a7,
0xb3ea28b2,0x33c32bc6,0x28b233ea,0x2bc6b3c3,0x301d32dd,0x28b233ea,0x32ddb01d,0x33eaa8b2,0x30c4b26d,0xb2dd301d,0xb26db0c4,0x301d32dd,
0xb3c3abc6,0xb26db0c4,0xabc633c3,0xb0c4326d,0x330eaf8b,0xb3f62646,0xb30e2f8b,0x33f6a646,0xb3a8aca5,0xb22fb113,0x33a82ca5,0x322f3113,
0x2f8b330e,0xa646b3f6,0xaf8bb30e,0x264633f6,0x2ca5b3a8,0x3113b22f,0xaca533a8,0xb113322f,0xb15f31ed,0x333baed7,0xb1edb15f,0x2ed7333b,
0x333baed7,0x33fea248,0x2ed7333b,0x224833fe,0xb3fe2248,0x33882d64,0xa248b3fe,0xad643388,0x33882d64,0x31ed315f,0xad643388,0xb15f31ed,
0x34000000,0xb364ae1f,0x34000000,0xb364ae1f,0x34000000,0x33642e1f,0x34000000,0x33642e1f,0x34000000,0xb364ae1f,0x34000000,0xb364ae1f,
0x34000000,0x33642e1f,0x34000000,0x33642e1f,0x3388ad64,0xb3fea248,0xad64b388,0xa24833fe,0x31edb15f,0x3388ad64,0xb15fb1ed,0xad64b388,
0x2ed7b33b,0xb1ed315f,0xb33baed7,0x315f31ed,0x2248b3fe,0x2ed7b33b,0xb3fea248,0xb33baed7,0x322fb113,0xb3a82ca5,0xb22f3113,0x33a8aca5,
0x2646b3f6,0x2f8bb30e,0xa64633f6,0xaf8b330e,0xb113b22f,0x2ca533a8,0x3113322f,0xaca5b3a8,0xb3f6a646,0xb30eaf8b,0x33f62646,0x330e2f8b,
0x301db2dd,0xb26d30c4,0x32dd301d,0xb0c4b26d,0xb0c4b26d,0xabc6b3c3,0x326db0c4,0x33c3abc6,0xb3c32bc6,0x33ea28b2,0xabc6b3c3,0xa8b233ea,
0xa8b233ea,0xb01d32dd,0xb3eaa8b2,0xb2ddb01d,0x2a3eb3d9,0xb07232a7,0x2a3eb3d9,0xb07232a7,0xb3d9aa3e,0xb2a7b072,0xb3d9aa3e,0xb2a7b072,
0xaa3e33d9,0x3072b2a7,0xaa3e33d9,0x3072b2a7,0x33d92a3e,0x32a73072,0x33d92a3e,0x32a73072,0xa8b2b3ea,0xabc633c3,0xb3ea28b2,0x33c32bc6,
0xb2dd301d,0xb3ea28b2,0x301d32dd,0x28b233ea,0x326d30c4,0xb01db2dd,0x30c4b26d,0xb2dd301d,0x2bc6b3c3,0x30c4b26d,0xb3c3abc6,0xb26db0c4,
0xaf8bb30e,0x264633f6,0x2f8b330e,0xa646b3f6,0xaca533a8,0xb113322f,0x2ca5b3a8,0x3113b22f,0x330eaf8b,0xb3f62646,0xb30e2f8b,0x33f6a646,
0xb3a8aca5,0xb22fb113,0x33a82ca5,0x322f3113,0xb1edb15f,0x2ed7333b,0x315fb1ed,0xb33b2ed7,0x2ed7333b,0x224833fe,0xb33b2ed7,0xb3fe2248,
0xa248b3fe,0xad643388,0x33fea248,0xb388ad64,0xad643388,0xb15f31ed,0xb388ad64,0xb1edb15f,0x34000000,0xb364ae1f,0x34000000,0xb364ae1f,
0x34000000,0x33642e1f,0x34000000,0x33642e1f,0x34000000,0xb364ae1f,0x34000000,0xb364ae1f,0x34000000,0x33642e1f,0x34000000,0x33642e1f,
0xb3882d64,0x33fe2248,0x2d643388,0x2248b3fe,0xb1ed315f,0xb3882d64,0x315f31ed,0x2d643388,0xaed7333b,0x31edb15f,0x333b2ed7,0xb15fb1ed,
0xa24833fe,0xaed7333b,0x33fe2248,0x333b2ed7,0x322fb113,0xb3a82ca5,0xb22f3113,0x33a8aca5,0x2646b3f6,0x2f8bb30e,0xa64633f6,0xaf8b330e,
0xb113b22f,0x2ca533a8,0x3113322f,0xaca5b3a8,0xb3f6a646,0xb30eaf8b,0x33f62646,0x330e2f8b,0xb01d32dd,0x326db0c4,0xb2ddb01d,0x30c4326d,
0x30c4326d,0x2bc633c3,0xb26d30c4,0xb3c32bc6,0x33c3abc6,0xb3eaa8b2,0x2bc633c3,0x28b2b3ea,0x28b2b3ea,0x301db2dd,0x33ea28b2,0x32dd301d,
0x2a3eb3d9,0xb07232a7,0x2a3eb3d9,0xb07232a7,0xb3d9aa3e,0xb2a7b072,0xb3d9aa3e,0xb2a7b072,0xaa3e33d9,0x3072b2a7,0xaa3e33d9,0x3072b2a7,
0x33d92a3e,0x32a73072,0x33d92a3e,0x32a73072,0x28b233ea,0x2bc6b3c3,0x33eaa8b2,0xb3c3abc6,0x32ddb01d,0x33eaa8b2,0xb01db2dd,0xa8b2b3ea,
0xb26db0c4,0x301d32dd,0xb0c4326d,0x32ddb01d,0xabc633c3,0xb0c4326d,0x33c32bc6,0x326d30c4,0xaf8bb30e,0x264633f6,0x2f8b330e,0xa646b3f6,
0xaca533a8,0xb113322f,0x2ca5b3a8,0x3113b22f,0x330eaf8b,0xb3f62646,0xb30e2f8b,0x33f6a646,0xb3a8aca5,0xb22fb113,0x33a82ca5,0x322f3113,
0x31ed315f,0xaed7b33b,0xb15f31ed,0x333baed7,0xaed7b33b,0xa248b3fe,0x333baed7,0x33fea248,0x224833fe,0x2d64b388,0xb3fe2248,0x33882d64,
0x2d64b388,0x315fb1ed,0x33882d64,0x31ed315f,0x3e80,0xbdac3e71,0xbdc4be6d,0xbc49be80,0xbe223e46,0xbe5c3e04,0x3d95be75,0x3e18be4e,
0xbe7b3d48,0xbe7dbd16,0x3e55be0e,0x3e78bd79,0xbe62bdf1,0xbe2cbe3e,0x3e7f3cc9,0x3e673ddb,0x3e800000,0x3e713dac,0xbe6d3dc4,0xbe803c49,
0x3e463e22,0x3e043e5c,0xbe75bd95,0xbe4ebe18,0x3d483e7b,0xbd163e7d,0xbe0ebe55,0xbd79be78,0xbdf13e62,0xbe3e3e2c,0x3cc9be7f,0x3ddbbe67,
0x3e80,0xbe2c3e3e,0x3dc43e6d,0xbdac3e71,0xbe7f3cc9,0xbe4ebe18,0xbe623df1,0xbe78bd79,0xbd48be7b,0x3e04be5c,0xbe0ebe55,0x3d16be7d,
0x3e75bd95,0x3e673ddb,0x3e46be22,0x3e803c49,0x3e800000,0x3e3e3e2c,0x3e6dbdc4,0x3e713dac,0x3cc93e7f,0xbe183e4e,0x3df13e62,0xbd793e78,
0xbe7b3d48,0xbe5cbe04,0xbe553e0e,0xbe7dbd16,0xbd95be75,0x3ddbbe67,0xbe22be46,0x3c49be80,0x3e80,0xbe673ddb,0xbdc4be6d,0x3e2cbe3e,
0xbe46be22,0x3d79be78,0x3e753d95,0x3d163e7d,0x3e7bbd48,0x3e183e4e,0xbe553e0e,0xbe5cbe04,0xbdf13e62,0xbe80bc49,0x3cc9be7f,0x3e71bdac,
0x3e800000,0x3ddb3e67,0xbe6d3dc4,0xbe3ebe2c,0xbe223e46,0xbe78bd79,0x3d95be75,0x3e7dbd16,0xbd48be7b,0x3e4ebe18,0x3e0e3e55,0xbe043e5c,
0x3e623df1,0xbc493e80,0xbe7fbcc9,0xbdacbe71,0x3e80,0xbe803c49,0x3dc43e6d,0xbe673ddb,0xbcc9be7f,0x3e7dbd16,0xbdf1be62,0x3e5cbe04,
0x3d483e7b,0xbe783d79,0x3e0e3e55,0xbe4e3e18,0xbd95be75,0x3e71bdac,0xbe22be46,0x3e3ebe2c,0x3e800000,0x3c493e80,0x3e6dbdc4,0x3ddb3e67,
0xbe7f3cc9,0xbd16be7d,0xbe623df1,0xbe04be5c,0x3e7bbd48,0x3d793e78,0x3e55be0e,0x3e183e4e,0xbe753d95,0xbdacbe71,0xbe463e22,0xbe2cbe3e,
0x3e80,0xbe71bdac,0xbdc4be6d,0x3e80bc49,0x3e22be46,0x3e043e5c,0xbd953e75,0xbe4ebe18,0xbe7b3d48,0x3d16be7d,0x3e55be0e,0x3d793e78,
0x3e623df1,0xbe3e3e2c,0xbe7fbcc9,0x3ddbbe67,0x3e800000,0xbdac3e71,0xbe6d3dc4,0xbc49be80,0xbe46be22,0x3e5cbe04,0x3e753d95,0xbe183e4e,
0x3d483e7b,0xbe7dbd16,0xbe0ebe55,0x3e78bd79,0x3df1be62,0x3e2c3e3e,0xbcc93e7f,0xbe67bddb,0x3e80,0xbe3ebe2c,0x3dc43e6d,0xbe71bdac,
0x3e7fbcc9,0xbe183e4e,0x3e62bdf1,0xbd793e78,0xbd48be7b,0x3e5c3e04,0xbe0ebe55,0x3e7d3d16,0xbe753d95,0x3ddbbe67,0xbe463e22,0x3c49be80,
0x3e800000,0xbe2c3e3e,0x3e6dbdc4,0xbdac3e71,0xbcc9be7f,0x3e4e3e18,0xbdf1be62,0x3e783d79,0xbe7b3d48,0x3e04be5c,0xbe553e0e,0x3d16be7d,
0x3d953e75,0xbe67bddb,0x3e223e46,0xbe80bc49,0x3e80,0xbddbbe67,0xbdc4be6d,0x3e3e3e2c,0x3e463e22,0xbe78bd79,0xbe75bd95,0x3e7dbd16,
0x3e7bbd48,0xbe4e3e18,0xbe553e0e,0x3e04be5c,0x3df1be62,0xbc493e80,0xbcc93e7f,0xbdacbe71,0x3e800000,0xbe673ddb,0xbe6d3dc4,0x3e2cbe3e,
0x3e22be46,0xbd793e78,0xbd953e75,0xbd16be7d,0xbd48be7b,0x3e183e4e,0x3e0e3e55,0xbe5cbe04,0xbe62bdf1,0x3e803c49,0x3e7f3cc9,0xbe713dac,
0x3e80,0xbc49be80,0x3dc43e6d,0xbddbbe67,0x3cc93e7f,0xbd16be7d,0x3df13e62,0xbe04be5c,0x3d483e7b,0xbd79be78,0x3e0e3e55,0xbe18be4e,
0x3d953e75,0xbdacbe71,0x3e223e46,0xbe2cbe3e,0x3e800000,0xbe803c49,0x3e6dbdc4,0xbe673ddb,0x3e7fbcc9,0xbe7d3d16,0x3e62bdf1,0xbe5c3e04,
0x3e7bbd48,0xbe783d79,0x3e55be0e,0xbe4e3e18,0x3e75bd95,0xbe713dac,0x3e46be22,0xbe3e3e2c,0x3e80,0x3dacbe71,0xbdc4be6d,0x3c493e80,
0xbe223e46,0x3e5cbe04,0x3d95be75,0xbe183e4e,0xbe7b3d48,0x3e7d3d16,0x3e55be0e,0xbe783d79,0xbe62bdf1,0x3e2c3e3e,0x3e7f3cc9,0xbe67bddb,
0x3e800000,0xbe71bdac,0xbe6d3dc4,0x3e80bc49,0x3e463e22,0xbe04be5c,0xbe75bd95,0x3e4e3e18,0x3d483e7b,0x3d16be7d,0xbe0ebe55,0x3d793e78,
0xbdf13e62,0x3e3ebe2c,0x3cc9be7f,0xbddb3e67,0x3e80,0x3e2cbe3e,0x3dc43e6d,0x3dacbe71,0xbe7f3cc9,0x3e4e3e18,0xbe623df1,0x3e783d79,
0xbd48be7b,0xbe043e5c,0xbe0ebe55,0xbd163e7d,0x3e75bd95,0xbe67bddb,0x3e46be22,0xbe80bc49,0x3e800000,0xbe3ebe2c,0x3e6dbdc4,0xbe71bdac,
0x3cc93e7f,0x3e18be4e,0x3df13e62,0x3d79be78,0xbe7b3d48,0x3e5c3e04,0xbe553e0e,0x3e7d3d16,0xbd95be75,0xbddb3e67,0xbe22be46,0xbc493e80,
0x3e80,0x3e67bddb,0xbdc4be6d,0xbe2c3e3e,0xbe46be22,0xbd793e78,0x3e753d95,0xbd16be7d,0x3e7bbd48,0xbe18be4e,0xbe553e0e,0x3e5c3e04,
0xbdf13e62,0x3e803c49,0x3cc9be7f,0xbe713dac,0x3e800000,0xbddbbe67,0xbe6d3dc4,0x3e3e3e2c,0xbe223e46,0x3e783d79,0x3d95be75,0xbe7d3d16,
0xbd48be7b,0xbe4e3e18,0x3e0e3e55,0x3e04be5c,0x3e623df1,0x3c49be80,0xbe7fbcc9,0x3dac3e71,0x3e80,0x3e80bc49,0x3dc43e6d,0x3e67bddb,
0xbcc9be7f,0xbe7d3d16,0xbdf1be62,0xbe5c3e04,0x3d483e7b,0x3e78bd79,0x3e0e3e55,0x3e4ebe18,0xbd95be75,0xbe713dac,0xbe22be46,0xbe3e3e2c,
0x3e800000,0xbc49be80,0x3e6dbdc4,0xbddbbe67,0xbe7f3cc9,0x3d163e7d,0xbe623df1,0x3e043e5c,0x3e7bbd48,0xbd79be78,0x3e55be0e,0xbe18be4e,
0xbe753d95,0x3dac3e71,0xbe463e22,0x3e2c3e3e,0x3e80,0x3e713dac,0xbdc4be6d,0xbe803c49,0x3e22be46,0xbe04be5c,0xbd953e75,0x3e4e3e18,
0xbe7b3d48,0xbd163e7d,0x3e55be0e,0xbd79be78,0x3e623df1,0x3e3ebe2c,0xbe7fbcc9,0xbddb3e67,0x3e800000,0x3dacbe71,0xbe6d3dc4,0x3c493e80,
0xbe46be22,0xbe5c3e04,0x3e753d95,0x3e18be4e,0x3d483e7b,0x3e7d3d16,0xbe0ebe55,0xbe783d79,0x3df1be62,0xbe2cbe3e,0xbcc93e7f,0x3e673ddb,
0x3e80,0x3e3e3e2c,0x3dc43e6d,0x3e713dac,0x3e7fbcc9,0x3e18be4e,0x3e62bdf1,0x3d79be78,0xbd48be7b,0xbe5cbe04,0xbe0ebe55,0xbe7dbd16,
0xbe753d95,0xbddb3e67,0xbe463e22,0xbc493e80,0x3e800000,0x3e2cbe3e,0x3e6dbdc4,0x3dacbe71,0xbcc9be7f,0xbe4ebe18,0xbdf1be62,0xbe78bd79,
0xbe7b3d48,0xbe043e5c,0xbe553e0e,0xbd163e7d,0x3d953e75,0x3e673ddb,0x3e223e46,0x3e803c49,0x3e80,0x3ddb3e67,0xbdc4be6d,0xbe3ebe2c,
0x3e463e22,0x3e783d79,0xbe75bd95,0xbe7d3d16,0x3e7bbd48,0x3e4ebe18,0xbe553e0e,0xbe043e5c,0x3df1be62,0x3c49be80,0xbcc93e7f,0x3dac3e71,
0x3e800000,0x3e67bddb,0xbe6d3dc4,0xbe2c3e3e,0x3e22be46,0x3d79be78,0xbd953e75,0x3d163e7d,0xbd48be7b,0xbe18be4e,0x3e0e3e55,0x3e5c3e04,
0xbe62bdf1,0xbe80bc49,0x3e7f3cc9,0x3e71bdac,0x3e80,0x3c493e80,0x3dc43e6d,0x3ddb3e67,0x3cc93e7f,0x3d163e7d,0x3df13e62,0x3e043e5c,
0x3d483e7b,0x3d793e78,0x3e0e3e55,0x3e183e4e,0x3d953e75,0x3dac3e71,0x3e223e46,0x3e2c3e3e,0x3e800000,0x3e80bc49,0x3e6dbdc4,0x3e67bddb,
0x3e7fbcc9,0x3e7dbd16,0x3e62bdf1,0x3e5cbe04,0x3e7bbd48,0x3e78bd79,0x3e55be0e,0x3e4ebe18,0x3e75bd95,0x3e71bdac,0x3e46be22,0x3e3ebe2c,
};


struct Maps { CUtensorMap w[4], gu[4], dn[2], a[2], h; };

__device__ __forceinline__ uint32_t s2u(const void* p) { return (uint32_t)__cvta_generic_to_shared(p); }
__device__ __forceinline__ void mbar_init(uint32_t a, int c) { asm volatile("mbarrier.init.shared::cta.b64 [%0], %1;" ::"r"(a), "r"(c) : "memory"); }
__device__ __forceinline__ void mbar_expect(uint32_t a, uint32_t b) { asm volatile("mbarrier.arrive.expect_tx.shared::cta.b64 _, [%0], %1;" ::"r"(a), "r"(b) : "memory"); }
__device__ __forceinline__ void mbar_arrive(uint32_t a) { asm volatile("mbarrier.arrive.shared::cta.b64 _, [%0];" ::"r"(a) : "memory"); }
__device__ __forceinline__ void mbar_arrive_remote(uint32_t a) { asm volatile("mbarrier.arrive.shared::cluster.b64 _, [%0];" ::"r"(a) : "memory"); }
__device__ __forceinline__ void mbar_wait(uint32_t a, uint32_t ph) {
  asm volatile("{\n.reg .pred p;\n.reg .u32 n;\nmov.u32 n, 0;\n"
               "L_w:\nmbarrier.try_wait.parity.shared::cta.b64 p, [%0], %1;\n@p bra L_d;\n"
               "add.u32 n, n, 1;\nsetp.lt.u32 p, n, 262144;\n@p bra L_w;\ntrap;\nL_d:\n}\n" ::"r"(a), "r"(ph) : "memory");
}
__device__ __forceinline__ void mbar_wait_cluster(uint32_t a, uint32_t ph) {
  asm volatile("{\n.reg .pred p;\n.reg .u32 n;\nmov.u32 n, 0;\n"
               "L_w:\nmbarrier.try_wait.parity.acquire.cluster.shared::cta.b64 p, [%0], %1;\n@p bra L_d;\n"
               "add.u32 n, n, 1;\nsetp.lt.u32 p, n, 262144;\n@p bra L_w;\ntrap;\nL_d:\n}\n" ::"r"(a), "r"(ph) : "memory");
}
__device__ __forceinline__ bool mbar_try(uint32_t a, uint32_t ph) {
  uint32_t ok;
  asm volatile("{\n.reg .pred p;\nmbarrier.test_wait.parity.shared::cta.b64 p, [%1], %2;\nselp.u32 %0, 1, 0, p;\n}\n" : "=r"(ok) : "r"(a), "r"(ph) : "memory");
  if (!ok) __nanosleep(40);
  return __all_sync(0xffffffffu, ok);
}
__device__ __forceinline__ void spin_guard(int& it) {
  ++it;
  asm volatile("{\n.reg .pred p;\nsetp.gt.s32 p, %0, 1048576;\n@p trap;\n}\n" ::"r"(it));
}
__device__ __forceinline__ bool elect_one() {
  uint32_t p;
  asm volatile("{\n.reg .pred p;\nelect.sync _|p, 0xffffffff;\nselp.u32 %0, 1, 0, p;\n}\n" : "=r"(p));
  return p != 0;
}
__device__ __forceinline__ void bar_sync(int id, int n) { asm volatile("bar.sync %0, %1;" ::"r"(id), "r"(n) : "memory"); }
__device__ __forceinline__ void bar_arrive(int id, int n) { asm volatile("bar.arrive %0, %1;" ::"r"(id), "r"(n) : "memory"); }
__device__ __forceinline__ uint32_t mapa(uint32_t a, uint32_t r) { uint32_t o; asm volatile("mapa.shared::cluster.u32 %0, %1, %2;" : "=r"(o) : "r"(a), "r"(r)); return o; }
__device__ __forceinline__ void tma2d(uint32_t dst, const CUtensorMap* m, uint32_t bar, int c0, int c1) {
  asm volatile("cp.async.bulk.tensor.2d.shared::cluster.global.mbarrier::complete_tx::bytes [%0], [%1, {%3, %4}], [%2];"
               ::"r"(dst), "l"(m), "r"(bar), "r"(c0), "r"(c1) : "memory");
}
__device__ __forceinline__ void tma3d(uint32_t dst, const CUtensorMap* m, uint32_t bar, int c0, int c1, int c2) {
  asm volatile("cp.async.bulk.tensor.3d.shared::cluster.global.mbarrier::complete_tx::bytes [%0], [%1, {%3, %4, %5}], [%2];"
               ::"r"(dst), "l"(m), "r"(bar), "r"(c0), "r"(c1), "r"(c2) : "memory");
}
__device__ __forceinline__ void tma_pf(const CUtensorMap* m, int c0, int c1) {
  asm volatile("cp.async.bulk.prefetch.tensor.2d.L2.global [%0, {%1, %2}];" ::"l"(m), "r"(c0), "r"(c1) : "memory");
}
__device__ __forceinline__ void bulk_g2s(uint32_t dst, const void* src, uint32_t bytes, uint32_t bar) {
  asm volatile("cp.async.bulk.shared::cluster.global.mbarrier::complete_tx::bytes [%0], [%1], %2, [%3];"
               ::"r"(dst), "l"(src), "r"(bytes), "r"(bar) : "memory");
}
__device__ __forceinline__ unsigned ld_relaxed(const unsigned* p) { unsigned v; asm volatile("ld.relaxed.gpu.global.u32 %0, [%1];" : "=r"(v) : "l"(p) : "memory"); return v; }
__device__ __forceinline__ void st_relaxed(unsigned* p, unsigned v) { asm volatile("st.relaxed.gpu.global.u32 [%0], %1;" ::"l"(p), "r"(v) : "memory"); }
__device__ __forceinline__ void red_add(unsigned* p, unsigned v) { asm volatile("red.relaxed.gpu.global.add.u32 [%0], %1;" ::"l"(p), "r"(v) : "memory"); }
__device__ __forceinline__ void stg_relaxed4(uint4* p, uint32_t a, uint32_t b, uint32_t c, uint32_t d) {
  asm volatile("st.relaxed.gpu.global.v4.u32 [%0], {%1,%2,%3,%4};" ::"l"(p), "r"(a), "r"(b), "r"(c), "r"(d) : "memory");
}
__device__ __forceinline__ void sts4(uint32_t a, uint32_t x, uint32_t y, uint32_t z, uint32_t w) {
  asm volatile("st.shared.v4.u32 [%0], {%1,%2,%3,%4};" ::"r"(a), "r"(x), "r"(y), "r"(z), "r"(w) : "memory");
}
__device__ __forceinline__ void lds4(uint32_t (&v)[4], uint32_t a) {
  asm volatile("ld.shared.v4.u32 {%0,%1,%2,%3}, [%4];" : "=r"(v[0]), "=r"(v[1]), "=r"(v[2]), "=r"(v[3]) : "r"(a) : "memory");
}
__device__ __forceinline__ uint32_t lds1(uint32_t a) { uint32_t v; asm volatile("ld.shared.u32 %0, [%1];" : "=r"(v) : "r"(a) : "memory"); return v; }
template <bool BF> __device__ __forceinline__ uint32_t pk(float lo, float hi) {
  uint32_t r;
  if (BF) asm("cvt.rn.bf16x2.f32 %0, %1, %2;" : "=r"(r) : "f"(hi), "f"(lo));
  else    asm("cvt.rn.f16x2.f32 %0, %1, %2;" : "=r"(r) : "f"(hi), "f"(lo));
  return r;
}
__device__ __forceinline__ float bf_lo(uint32_t v) { return __uint_as_float(v << 16); }
__device__ __forceinline__ float bf_hi(uint32_t v) { return __uint_as_float(v & 0xffff0000u); }
__device__ __forceinline__ uint32_t bf2_add(uint32_t a, uint32_t b) { uint32_t r; asm("add.rn.bf16x2 %0, %1, %2;" : "=r"(r) : "r"(a), "r"(b)); return r; }
__device__ __forceinline__ uint32_t bf2_mul(uint32_t a, uint32_t b) { uint32_t r; asm("mul.rn.bf16x2 %0, %1, %2;" : "=r"(r) : "r"(a), "r"(b)); return r; }
template <bool BF> __device__ __forceinline__ void mma16816(float (&d)[4], uint32_t a0, uint32_t a1, uint32_t a2, uint32_t a3, uint32_t b0, uint32_t b1) {
  if (BF) asm("mma.sync.aligned.m16n8k16.row.col.f32.bf16.bf16.f32 {%0,%1,%2,%3}, {%4,%5,%6,%7}, {%8,%9}, {%0,%1,%2,%3};"
                       : "+f"(d[0]), "+f"(d[1]), "+f"(d[2]), "+f"(d[3]) : "r"(a0), "r"(a1), "r"(a2), "r"(a3), "r"(b0), "r"(b1));
  else    asm("mma.sync.aligned.m16n8k16.row.col.f32.f16.f16.f32 {%0,%1,%2,%3}, {%4,%5,%6,%7}, {%8,%9}, {%0,%1,%2,%3};"
                       : "+f"(d[0]), "+f"(d[1]), "+f"(d[2]), "+f"(d[3]) : "r"(a0), "r"(a1), "r"(a2), "r"(a3), "r"(b0), "r"(b1));
}
#define tensor_keepalive() do { asm volatile("mma.sync.aligned.m16n8k8.row.col.f32.bf16.bf16.f32 {%0,%1,%2,%3}, {%4,%4}, {%4}, {%0,%1,%2,%3};" \
    : "+f"(ka[0]), "+f"(ka[1]), "+f"(ka[2]), "+f"(ka[3]) : "r"(0u)); } while (0)
template <int N> __device__ __forceinline__ void cexp(int m, float& co, float& si) {
  int q = ((m & (N - 1)) ^ (N / 2)) - N / 2;
  __sincosf((float)q * (6.283185307179586f / N), &si, &co);
}
__device__ __forceinline__ void sts1(uint32_t a, uint32_t v) { asm volatile("st.shared.u32 [%0], %1;" ::"r"(a), "r"(v) : "memory"); }
template <bool BF> __device__ __forceinline__ void put_a(uint32_t base, int lane, int t, int x, float co, float si, float sg) {
  const uint32_t a = base + t * 512 + lane * 16 + x * 4;
  sts1(a, pk<BF>(co, -si * sg)); sts1(a + 1024, pk<BF>(si, co * sg));
}
template <bool BF> __device__ __forceinline__ void put_b(uint32_t base, int jj, int j, int quad, int word, float co, float si, float sg) {
  const uint32_t a = base + quad * 512 + (8 * jj + j) * 16 + word * 4;
  sts1(a, pk<BF>(co, -si)); sts1(a + 64, pk<BF>(si * sg, co * sg));
}
__device__ __forceinline__ void get_a(uint32_t (&A)[2][2][4], uint32_t base, int lane) {
#pragma unroll
  for (int q = 0; q < 4; q++) lds4(A[q >> 1][q & 1], base + q * 512 + lane * 16);
}
__device__ __forceinline__ void get_b(uint32_t (&B)[4][2][2], uint32_t base, int lane) {
#pragma unroll
  for (int q = 0; q < 4; q++) {
    uint32_t v[4]; lds4(v, base + q * 512 + lane * 16);
    B[q][0][0] = v[0]; B[q][0][1] = v[1]; B[q][1][0] = v[2]; B[q][1][1] = v[3];
  }
}
__device__ __forceinline__ void get_tw(float (&tw)[2][4][2], uint32_t base, int lane) {
#pragma unroll
  for (int q = 0; q < 4; q++) {
    uint32_t v[4]; lds4(v, base + q * 512 + lane * 16);
    tw[q >> 1][2 * (q & 1)][0] = __uint_as_float(v[0]); tw[q >> 1][2 * (q & 1)][1] = __uint_as_float(v[1]);
    tw[q >> 1][2 * (q & 1) + 1][0] = __uint_as_float(v[2]); tw[q >> 1][2 * (q & 1) + 1][1] = __uint_as_float(v[3]);
  }
}

constexpr uint32_t DESC_HI = 0x40000040u;
__device__ __forceinline__ void wgmma_ss_n224(float (&d)[112], uint32_t da, uint32_t db, int sd) {
  asm volatile("{\n.reg .pred p;\n.reg .b64 da, db;\nsetp.ne.b32 p, %114, 0;\nmov.b64 da, {%112, %115};\nmov.b64 db, {%113, %115};\n"
    "wgmma.mma_async.sync.aligned.m64n224k16.f32.bf16.bf16 "
    "{%0, %1, %2, %3, %4, %5, %6, %7, %8, %9, %10, %11, %12, %13, %14, %15, %16, %17, %18, %19, %20, %21, "
    "%22, %23, %24, %25, %26, %27, %28, %29, %30, %31, %32, %33, %34, %35, %36, %37, %38, %39, %40, %41, "
    "%42, %43, %44, %45, %46, %47, %48, %49, %50, %51, %52, %53, %54, %55, %56, %57, %58, %59, %60, %61, "
    "%62, %63, %64, %65, %66, %67, %68, %69, %70, %71, %72, %73, %74, %75, %76, %77, %78, %79, %80, %81, "
    "%82, %83, %84, %85, %86, %87, %88, %89, %90, %91, %92, %93, %94, %95, %96, %97, %98, %99, %100, %101, "
    "%102, %103, %104, %105, %106, %107, %108, %109, %110, %111}, da, db, p, 1, 1, 0, 1;\n}\n"
    : "+f"(d[0]), "+f"(d[1]), "+f"(d[2]), "+f"(d[3]), "+f"(d[4]), "+f"(d[5]), "+f"(d[6]), "+f"(d[7]),
      "+f"(d[8]), "+f"(d[9]), "+f"(d[10]), "+f"(d[11]), "+f"(d[12]), "+f"(d[13]), "+f"(d[14]), "+f"(d[15]),
      "+f"(d[16]), "+f"(d[17]), "+f"(d[18]), "+f"(d[19]), "+f"(d[20]), "+f"(d[21]), "+f"(d[22]), "+f"(d[23]),
      "+f"(d[24]), "+f"(d[25]), "+f"(d[26]), "+f"(d[27]), "+f"(d[28]), "+f"(d[29]), "+f"(d[30]), "+f"(d[31]),
      "+f"(d[32]), "+f"(d[33]), "+f"(d[34]), "+f"(d[35]), "+f"(d[36]), "+f"(d[37]), "+f"(d[38]), "+f"(d[39]),
      "+f"(d[40]), "+f"(d[41]), "+f"(d[42]), "+f"(d[43]), "+f"(d[44]), "+f"(d[45]), "+f"(d[46]), "+f"(d[47]),
      "+f"(d[48]), "+f"(d[49]), "+f"(d[50]), "+f"(d[51]), "+f"(d[52]), "+f"(d[53]), "+f"(d[54]), "+f"(d[55]),
      "+f"(d[56]), "+f"(d[57]), "+f"(d[58]), "+f"(d[59]), "+f"(d[60]), "+f"(d[61]), "+f"(d[62]), "+f"(d[63]),
      "+f"(d[64]), "+f"(d[65]), "+f"(d[66]), "+f"(d[67]), "+f"(d[68]), "+f"(d[69]), "+f"(d[70]), "+f"(d[71]),
      "+f"(d[72]), "+f"(d[73]), "+f"(d[74]), "+f"(d[75]), "+f"(d[76]), "+f"(d[77]), "+f"(d[78]), "+f"(d[79]),
      "+f"(d[80]), "+f"(d[81]), "+f"(d[82]), "+f"(d[83]), "+f"(d[84]), "+f"(d[85]), "+f"(d[86]), "+f"(d[87]),
      "+f"(d[88]), "+f"(d[89]), "+f"(d[90]), "+f"(d[91]), "+f"(d[92]), "+f"(d[93]), "+f"(d[94]), "+f"(d[95]),
      "+f"(d[96]), "+f"(d[97]), "+f"(d[98]), "+f"(d[99]), "+f"(d[100]), "+f"(d[101]), "+f"(d[102]), "+f"(d[103]),
      "+f"(d[104]), "+f"(d[105]), "+f"(d[106]), "+f"(d[107]), "+f"(d[108]), "+f"(d[109]), "+f"(d[110]), "+f"(d[111])
    : "r"(da), "r"(db), "r"(sd), "n"(DESC_HI));
}
__device__ __forceinline__ void wgmma_rs_n64(float (&d)[32], const uint32_t (&a)[4], uint32_t db, int sd) {
  asm volatile("{\n.reg .pred p;\n.reg .b64 da, db;\nsetp.ne.b32 p, %37, 0;\nmov.b64 db, {%36, %38};\n"
    "wgmma.mma_async.sync.aligned.m64n64k16.f32.bf16.bf16 "
    "{%0, %1, %2, %3, %4, %5, %6, %7, %8, %9, %10, %11, %12, %13, %14, %15, %16, %17, %18, %19, %20, %21, "
    "%22, %23, %24, %25, %26, %27, %28, %29, %30, %31}, {%32, %33, %34, %35}, db, p, 1, 1, 1;\n}\n"
    : "+f"(d[0]), "+f"(d[1]), "+f"(d[2]), "+f"(d[3]), "+f"(d[4]), "+f"(d[5]), "+f"(d[6]), "+f"(d[7]),
      "+f"(d[8]), "+f"(d[9]), "+f"(d[10]), "+f"(d[11]), "+f"(d[12]), "+f"(d[13]), "+f"(d[14]), "+f"(d[15]),
      "+f"(d[16]), "+f"(d[17]), "+f"(d[18]), "+f"(d[19]), "+f"(d[20]), "+f"(d[21]), "+f"(d[22]), "+f"(d[23]),
      "+f"(d[24]), "+f"(d[25]), "+f"(d[26]), "+f"(d[27]), "+f"(d[28]), "+f"(d[29]), "+f"(d[30]), "+f"(d[31])
    : "r"(a[0]), "r"(a[1]), "r"(a[2]), "r"(a[3]), "r"(db), "r"(sd), "n"(DESC_HI));
}


__device__ __forceinline__ void wg_fence() { asm volatile("wgmma.fence.sync.aligned;" ::: "memory"); }
__device__ __forceinline__ void wg_commit() { asm volatile("wgmma.commit_group.sync.aligned;" ::: "memory"); }
template <int N> __device__ __forceinline__ void wg_wait() { asm volatile("wgmma.wait_group.sync.aligned %0;" ::"n"(N) : "memory"); }
template <int N> __device__ __forceinline__ void reg_fence(float (&d)[N]) {
#pragma unroll
  for (int i = 0; i < N; i++) asm volatile("" : "+f"(d[i])::"memory");
}
__device__ __forceinline__ uint32_t mkdesc(uint32_t addr, uint32_t lbo) { return ((addr & 0x3FFFF) >> 4) | ((lbo >> 4) << 16); }
__device__ __forceinline__ float silu(float g, float hr, float rs) {
  const float hgt = hr * g, hs = hgt * rs;
  float t; asm("tanh.approx.f32 %0, %1;" : "=f"(t) : "f"(hgt));
  return fmaf(hs, t, hs);
}
__device__ __forceinline__ uint32_t silu2(uint32_t g, float rs) { return pk<true>(silu(bf_lo(g), 0.5f * rs, rs), silu(bf_hi(g), 0.5f * rs, rs)); }

constexpr bool INV_BF = true;

template <bool BF> __device__ __forceinline__ void stage_dataB(float (&T)[4][2][4], const uint32_t (&A)[2][2][4], const uint32_t (&in)[4][4]) {
#pragma unroll
  for (int e = 0; e < 4; e++)
#pragma unroll
    for (int p = 0; p < 2; p++) {
#pragma unroll
      for (int x = 0; x < 4; x++) T[e][p][x] = 0.f;
#pragma unroll
      for (int t = 0; t < 2; t++) mma16816<BF>(T[e][p], A[p][t][0], A[p][t][1], A[p][t][2], A[p][t][3], in[2 * t][e], in[2 * t + 1][e]);
    }
}
template <bool BF> __device__ __forceinline__ void stage_dataA(float (&O)[2][4][4], const uint32_t (&B)[4][2][2], const uint32_t (&L)[2][2][4]) {
#pragma unroll
  for (int tau = 0; tau < 2; tau++)
#pragma unroll
    for (int v = 0; v < 4; v++) {
#pragma unroll
      for (int x = 0; x < 4; x++) O[tau][v][x] = 0.f;
#pragma unroll
      for (int t = 0; t < 2; t++) mma16816<BF>(O[tau][v], L[t][tau][0], L[t][tau][1], L[t][tau][2], L[t][tau][3], B[v][t][0], B[v][t][1]);
    }
}
template <bool BF> __device__ __forceinline__ void fft256a(float (&T)[2][2][2][4], const uint32_t (&z)[2][4][2], const uint32_t (&A1)[2][2][4]) {
#pragma unroll
  for (int t = 0; t < 2; t++)
#pragma unroll
    for (int u = 0; u < 2; u++)
#pragma unroll
      for (int uu = 0; uu < 2; uu++)
#pragma unroll
        for (int p = 0; p < 2; p++) {
          if (t == 0) { T[u][uu][p][0] = T[u][uu][p][1] = T[u][uu][p][2] = T[u][uu][p][3] = 0.f; }
          mma16816<BF>(T[u][uu][p], A1[p][t][0], A1[p][t][1], A1[p][t][2], A1[p][t][3], z[u][2 * t][uu], z[u][2 * t + 1][uu]);
        }
}
template <bool BF> __device__ __forceinline__ void fft256b(float (&O)[2][4][4], const float (&T)[2][2][2][4], const float (&tw)[2][4][2], const uint32_t (&B2)[4][2][2]) {
#pragma unroll
  for (int uu = 0; uu < 2; uu++)
#pragma unroll
    for (int u = 0; u < 2; u++) {
      uint32_t a[4];
#pragma unroll
      for (int x = 0; x < 4; x++) {
        const float re = T[u][uu][0][x] * tw[uu][x][0] - T[u][uu][1][x] * tw[uu][x][1];
        const float im = T[u][uu][0][x] * tw[uu][x][1] + T[u][uu][1][x] * tw[uu][x][0];
        a[x] = pk<BF>(re, im);
      }
#pragma unroll
      for (int v = 0; v < 4; v++) {
        if (uu == 0) { O[u][v][0] = O[u][v][1] = O[u][v][2] = O[u][v][3] = 0.f; }
        mma16816<BF>(O[u][v], a[0], a[2], a[1], a[3], B2[v][uu][0], B2[v][uu][1]);
      }
    }
}
__device__ __forceinline__ int rmap(int half, int c) { return half ? (c ? 16 - c : 8) : c; }

__device__ __forceinline__ void row_stats(const uint2 (&r)[2][4], float (&s1)[2], float (&s2)[2], int lane) {
  float d[2][2][4] = {};
#pragma unroll
  for (int i = 0; i < 4; i++)
#pragma unroll
    for (int u = 0; u < 2; u++) mma16816<true>(d[u][i & 1], r[u][i].x, 0x3f803f80u, r[u][i].y, 0x3f803f80u, r[u][i].x, r[u][i].y);
#pragma unroll
  for (int u = 0; u < 2; u++) {
    s1[u] = (d[u][0][2] + d[u][1][2]) + (d[u][0][3] + d[u][1][3]);
    s2[u] = (lane & 4) ? d[u][0][1] + d[u][1][1] : d[u][0][0] + d[u][1][0];
  }
#pragma unroll
  for (int u = 0; u < 2; u++) s2[u] = __shfl_sync(~0u, s2[u], 4 * (lane & 7) + ((lane & 7) >> 1));
#pragma unroll
  for (int o = 1; o < 8; o <<= 1)
#pragma unroll
    for (int u = 0; u < 2; u++) {
      if (o < 4) s1[u] += __shfl_xor_sync(~0u, s1[u], o);
      s2[u] += __shfl_xor_sync(~0u, s2[u], o);
    }
}
__device__ __forceinline__ float ldsw(uint32_t a) {
  unsigned short v; asm volatile("ld.shared.u16 %0, [%1];" : "=h"(v) : "r"(a) : "memory");
  return __uint_as_float((uint32_t)v << 16);
}
__device__ __forceinline__ void st_async4(uint32_t addr, const uint32_t (&v)[4], uint32_t mb) {
  asm volatile("st.async.weak.shared::cluster.mbarrier::complete_tx::bytes.v4.b32 [%0], {%1,%2,%3,%4}, [%5];"
               ::"r"(addr), "r"(v[0]), "r"(v[1]), "r"(v[2]), "r"(v[3]), "r"(mb) : "memory");
}
__device__ __forceinline__ void poll_counter(const unsigned* p, unsigned target) {
  int it = 0;
  while ((int)(ld_relaxed(p) - target) < 0) spin_guard(it);
}
__device__ __forceinline__ void check_tagged(uint32_t (&in)[4][4], const uint4* src, int stride, uint32_t tag) {
  int it = 0;
  while (__any_sync(0xffffffffu, ((in[0][0] ^ tag) | (in[1][0] ^ tag) | (in[2][0] ^ tag) | (in[3][0] ^ tag)) & 1u)) {
#pragma unroll
    for (int i = 0; i < 4; i++)
      asm volatile("ld.relaxed.gpu.global.v4.u32 {%0,%1,%2,%3}, [%4];" : "=r"(in[i][0]), "=r"(in[i][1]), "=r"(in[i][2]), "=r"(in[i][3])
                   : "l"(src + i * stride) : "memory");
    spin_guard(it);
  }
#pragma unroll
  for (int i = 0; i < 4; i++) in[i][0] &= ~1u;
}
__device__ __forceinline__ uint32_t pin32(uint32_t v) { return __shfl_sync(0xffffffffu, v, 0); }
template <class T> __device__ __forceinline__ T* pin64(T* p) { return (T*)__shfl_sync(0xffffffffu, (unsigned long long)p, 0); }
template <bool BF>
__device__ __forceinline__ void recv_stage(float (&T)[4][2][4], const uint32_t (&A)[2][2][4], uint32_t land, uint32_t mb, const uint4* src, uint32_t tag) {
  uint32_t in[4][4];
  int it = 0;
  mbar_wait(mb, 0);
#pragma unroll
  for (int i = 0; i < 4; i++) lds4(in[i], land + i * 4096);
  while (true) {
    const bool bad = __any_sync(0xffffffffu, ((in[0][0] ^ tag) | (in[1][0] ^ tag) | (in[2][0] ^ tag) | (in[3][0] ^ tag)) & 1u);
#pragma unroll
    for (int i = 0; i < 4; i++) in[i][0] &= ~1u;
    stage_dataB<BF>(T, A, in);
    if (!bad) break;
#pragma unroll
    for (int i = 0; i < 4; i++)
      asm volatile("ld.relaxed.gpu.global.v4.u32 {%0,%1,%2,%3}, [%4];" : "=r"(in[i][0]), "=r"(in[i][1]), "=r"(in[i][2]), "=r"(in[i][3])
                   : "l"(src + i * 256) : "memory");
    spin_guard(it);
  }
}

__global__ void __cluster_dims__(2, 1, 1) __launch_bounds__(384, 1)
fused_kernel(const __nv_bfloat16* __restrict__ x, Scratch* __restrict__ sc, const uint32_t* __restrict__ table, const char* __restrict__ wdown,
             __nv_bfloat16* __restrict__ out,
             const __grid_constant__ Maps maps) {
  extern __shared__ uint8_t smem_raw[];
  const int tid = threadIdx.x, lane = tid & 31;
  const int b = blockIdx.x;
  const int warp = __shfl_sync(0xffffffffu, tid >> 5, 0);
  const uint32_t sb = (s2u(smem_raw) + 1023u) & ~1023u;
  const uint32_t bar = sb + SM_BAR;
  const int mblk = b >> 3, jF = b & 7, r4 = jF >> 1, e_ = jF & 1;

  if (warp >= 8) {
    asm volatile("setmaxnreg.dec.sync.aligned.u32 40;");
    float ka[4] = {0.f, 0.f, 0.f, 0.f};
    const int fa = r4 * 448 + e_ * 256, fH = r4 * 448 + 192 + e_ * 32, fa2 = r4 * 448 + (e_ ^ 1) * 256, fH2 = r4 * 448 + 192 + (e_ ^ 1) * 32;
    if (warp == 11) {
      const int k1m = (16 - mblk) & 15;
      if (lane == 0) {
        mbar_init(bar + 8 * B_T, 1);
        mbar_expect(bar + 8 * B_T, (jF ? 4 * 6144 : 4 * 6144 + 4 * 2048) + 46080 - 6144);
      }
      asm volatile("fence.proxy.async.shared::cta;" ::: "memory");
      __syncwarp();
      bar_arrive(13, 352);
      if (elect_one()) {
        const int c0 = (WCOLS * mblk + 16 * jF) & ~7, c1 = (WCOLS * k1m + 241 - 16 * jF) & ~7;
        tma3d(sb + SM_W, &maps.w[0], bar + 8 * B_T, c0, 0, 0);
        tma3d(sb + SM_W + 6144, &maps.w[1], bar + 8 * B_T, c0, 0, 0);
        tma3d(sb + SM_W + 2 * 6144, &maps.w[0], bar + 8 * B_T, c1, 0, 0);
        tma3d(sb + SM_W + 3 * 6144, &maps.w[1], bar + 8 * B_T, c1, 0, 0);
        if (jF == 0) {
#pragma unroll
          for (int i = 0; i < 4; i++) tma3d(sb + SM_W + (4 + i) * 6144, &maps.w[2 + (i & 1)], bar + 8 * B_T, (WCOLS * mblk + (i < 2 ? 256 : 128)) & ~7, 0, 0);
        }
        bulk_g2s(sb + SM_CC, table + 1536, 46080 - 6144, bar + 8 * B_T);
      }
      __syncwarp();
    } else if (warp == 9) {
      if (lane == 0) {
#pragma unroll
        for (int i = 0; i < B_T; i++) mbar_init(bar + 8 * i, (i >= B_EMPTY && i < B_AFULL) ? 8 : ((i >> 2) == 5 ? 4 : 1));
        mbar_init(bar + 8 * B_LN, 9);
#pragma unroll
        for (int i = 0; i < 6; i++) mbar_expect(bar + 8 * (B_ACT + i), (i % 3) == 2 ? 12288 : 8192);
        asm volatile("fence.mbarrier_init.release.cluster;" ::: "memory");
      }
      __syncwarp();
      bar_arrive(13, 352);
      bar_arrive(12, 96);
      bar_arrive(2, 64);
    }
    else if (warp == 8) {
      tensor_keepalive();
      if (lane == 0) { mbar_init(bar + 8 * B_L0, 8); mbar_init(bar + 8 * B_RS, 1); }
      __syncwarp();
      bar_arrive(13, 352);
      bar_sync(2, 64);
    }
    asm volatile("barrier.cluster.arrive.relaxed.aligned;" ::: "memory");
    if (warp >= 10) {
      const int pw = (warp == 10);
      bar_sync(12, 96);
      {
        mbar_wait(bar + 8 * B_X, 0);
        if (!pw && elect_one()) { tma_pf(&maps.gu[0], fa, mblk * 32); tma_pf(&maps.gu[1], fa, mblk * 32); tma_pf(&maps.gu[0], fa + 64, mblk * 32); tma_pf(&maps.gu[2], fH, mblk * 32); }
        __syncwarp();
      }
      int slot = 0; uint32_t ph = 1;
#pragma unroll 1
      for (int st = 0; st < 32; st++) {
        const uint32_t dst = sb + SM_RING + slot * SLOT_BYTES + pw * 4096, fb = bar + 8 * (B_FULL + slot);
        if (st == 3) { mbar_wait(bar + 8 * (B_X + 1), 0); asm volatile("fence.proxy.async.shared::cta;" ::: "memory"); }
        if (st == NSLOT && pw) {
          mbar_wait(bar + 8 * B_LN, 0);
          if (lane < 16) st_relaxed(reinterpret_cast<unsigned*>(&sc->rstd[b * 16 + lane]), lds1(bar + 384 + lane * 4));
          __syncwarp();
          if (elect_one()) {
            asm volatile("cp.async.bulk.global.shared::cta.bulk_group [%0], [%1], %2;" ::"l"(sc->ln2 + S_ * 128 * SV + b * 16 * (512 - 128 * SV)), "r"(sb + SM_X), "n"(4096 * (4 - SV)) : "memory");
            asm volatile("cp.async.bulk.commit_group;" ::: "memory");
            asm volatile("cp.async.bulk.wait_group 0;" ::: "memory");
            asm volatile("fence.acq_rel.gpu;" ::: "memory");
            red_add(&sc->cntC[mblk * 32 + 16], 1);
          }
          __syncwarp();
        }
        const int p2 = st >> 4, k0 = (st & 15) * 32;
        mbar_wait(bar + 8 * (B_EMPTY + slot), ph);
        if (elect_one()) {
          if (!pw) mbar_expect(fb, 14336);
          tma2d(dst, &maps.gu[pw], fb, fa + 128 * p2, k0);
          tma2d(dst + 8192, &maps.gu[2 * pw + p2], fb, pw ? fH : fa + 64, k0);
        }
        if (++slot == NSLOT) { slot = 0; ph ^= 1; }
      }
#pragma unroll 1
      for (int n = 0; n < 16; n++) {
        const uint32_t dst = sb + SM_RING + slot * SLOT_BYTES + pw * 8192, fb = bar + 8 * (B_FULL + slot);
        const int t = (G2_T >> (2 * n)) & 3, qq = (G2_Q >> (2 * n)) & 3;
        const int col = e_ * 256 + ((r4 + 1 + t) & 3) * 64;
        const int k0 = pw ? (qq == 0 ? fa2 : (qq == 1 ? fH : (qq == 2 ? fa2 + 64 : fH2))) : (qq == 3 ? fa2 + 128 : fa + 64 * qq);
        mbar_wait(bar + 8 * (B_EMPTY + slot), ph);
        if (elect_one()) {
          if (!pw) mbar_expect(fb, (qq & 1) ? 12288 : 16384);
          tma2d(dst, &maps.dn[pw && (qq & 1)], fb, col, k0);
        }
        if (++slot == NSLOT) { slot = 0; ph ^= 1; }
      }
    } else if (warp == 9) {
      const unsigned ep = ld_relaxed(&sc->epoch) + 1;
      if (lane < 3) asm volatile("prefetch.tensormap [%0];" ::"l"(&maps.a[0] + lane) : "memory");
#pragma unroll 1
      for (int xch = 0; xch < 2; xch++) {
        if (lane == 0) mbar_expect(bar + 8 * (B_X + xch), 16384);
        const uint32_t xd = pin32(sb + SM_X), xb = pin32(bar + 8 * (B_X + xch));
        const uint4* xs = pin64(&sc->z1[(xch * NCTA + b) * 1024]);
        {
          int it = 0;
          const unsigned* cp = &sc->cnt[(xch * 256 + (lane & (NGRP - 1)) * NREP + (b & (NREP - 1))) * 32];
          while (__any_sync(0xffffffffu, (int)(ld_relaxed(cp) - ep * (NCTA / NGRP)) < 0)) spin_guard(it);
        }
        if (elect_one()) bulk_g2s(xd, xs, 16384, xb);
        __syncwarp();
      }
      if (lane < 8) mbar_expect(bar + 8 * (B_AFULL + lane), 16384);
#pragma unroll 1
      for (int part = 0; part < 2; part++) {
        const uint32_t ad = pin32(sb + SM_A + 4 * part * 16384 + e_ * 8192), ab = pin32(bar + 8 * (B_AFULL + 4 * part)), ar = pin32(mblk * 128 + e_ * 64);
        const CUtensorMap* am = pin64(&maps.a[part]);
        poll_counter(&sc->cntC[mblk * 32 + part * 16], ep * 8);
        if (elect_one()) {
#pragma unroll
          for (int i = 0; i < 4; i++)
            asm volatile("cp.async.bulk.tensor.2d.shared::cluster.global.mbarrier::complete_tx::bytes.multicast::cluster [%0], [%1, {%3, %4}], [%2], %5;"
                         ::"r"(ad + i * 16384), "l"(am), "r"(ab + 8 * i), "r"(i * 64), "r"(ar), "h"((uint16_t)3) : "memory");
        }
        __syncwarp();
        if (part == 0 && lane == 0) mbar_arrive(bar + 8 * B_LN);
      }
      bar_sync(5, 288);
      {
        int it = 0;
        while (__any_sync(0xffffffffu, ld_relaxed(&sc->flagH[mblk * 8 + (lane & 7)]) != ep)) spin_guard(it);
      }
      if (elect_one()) {
#pragma unroll
        for (int i = 0; i < 2; i++) {
          mbar_expect(bar + 8 * (B_PART + i), 8192);
          tma2d(sb + SM_A + 7 * 16384 + i * 8192, &maps.h, bar + 8 * (B_PART + i), e_ * 256 + r4 * 64, mblk * 128 + i * 64);
        }
      }
    } else {
      { int it = 0; do { tensor_keepalive(); spin_guard(it); } while (!mbar_try(bar + 8 * (B_X + 1), 0)); }
      unsigned* cc = pin64(&sc->cntC[mblk * 32]);
      mbar_wait(bar + 8 * B_L0, 0);
      tensor_keepalive();
      if (elect_one()) { asm volatile("fence.proxy.async;" ::: "memory"); red_add(cc, 1); }
      __syncwarp();
      { int it = 0; do { tensor_keepalive(); spin_guard(it); } while (!mbar_try(bar + 8 * B_AFULL, 0)); }
      if (ka[0] != 0.f) sts1(bar + 8 * B_NUM + 4, 0);
      const unsigned ep = lds1(bar + 8 * B_NUM);
      bar_sync(9, 288);
      if (elect_one()) {
        tma_pf(&maps.gu[0], fa + 128, mblk * 32); tma_pf(&maps.gu[1], fa + 128, mblk * 32); tma_pf(&maps.gu[1], fa + 64, mblk * 32); tma_pf(&maps.gu[3], fH, mblk * 32);
        asm volatile("cp.async.bulk.prefetch.L2.global [%0], %1;" ::"l"(wdown + (size_t)b * 14336), "r"(14336) : "memory");
      }
      __syncwarp();
#pragma unroll 1
      for (int i = 0; i < 32; i++) {
        stg_relaxed4(&sc->part[((mblk * 8 + ((r4 + 3) & 3) * 2 + e_) * 3 + 2) * 1024 + i * 32 + lane], 0, 0, 0, 0);
        __nanosleep(40);
      }
      bar_sync(10, 288);
      if (lane == 0) {
        asm volatile("fence.acq_rel.gpu;" ::: "memory");
        st_relaxed(&sc->flagH[b], ep);
        if (b == 0) st_relaxed(&sc->epoch, ep);
        mbar_arrive(bar + 8 * B_RS);
      }
    }
    __syncwarp();
    asm volatile("barrier.cluster.wait.acquire.aligned;" ::: "memory");
  } else {
    const int w = warp, c = lane >> 2, j = lane & 3;
    uint2 xr[2][4];
    {
      const __nv_bfloat16* xp = x + (size_t)(256 * w + b) * D_ + 32 * j + 4 * c;
#pragma unroll
      for (int u = 0; u < 2; u++)
#pragma unroll
        for (int i = 0; i < 4; i++)
          asm volatile("ld.global.nc.v2.u32 {%0,%1}, [%2];" : "=r"(xr[u][i].x), "=r"(xr[u][i].y) : "l"(xp + u * 128 * D_ + 128 * i));
    }
    uint32_t ca[12][4];
#pragma unroll
    for (int q = 0; q < 12; q++)
      asm volatile("ld.global.nc.v4.u32 {%0,%1,%2,%3}, [%4];" : "=r"(ca[q][0]), "=r"(ca[q][1]), "=r"(ca[q][2]), "=r"(ca[q][3]) : "l"(table + q * 128 + lane * 4));
    const unsigned ep = ld_relaxed(&sc->epoch) + 1;
    asm volatile("barrier.cluster.arrive.relaxed.aligned;" ::: "memory");
    const uint32_t E0 = sb + SM_A, E1 = E0 + 24576;
    {
      const int a = tid >> 4, q = tid & 15;
      float co, si;
      cexp<2048>(a * (128 * q + b), co, si); co *= 0.25f; si *= 0.25f;
      put_b<false>(sb + SM_BC, a & 3, (q >> 1) & 3, a >> 2, 2 * (q >> 3) + (q & 1), co, -si, 1.f);
      put_a<INV_BF>(sb + SM_AC, 4 * (q & 7) + (a & 3), a >> 3, (q >> 3) + 2 * ((a >> 2) & 1), co, si, 1.f);
    }
    bar_sync(13, 352);
    uint32_t BC[4][2][2];
    get_b(BC, sb + SM_BC, lane);
    asm volatile("setmaxnreg.inc.sync.aligned.u32 232;");
    const uint32_t tag = ep & 1u;
    float mean1[2];
    const int xo = (8 * j + w) * 8 + (c ^ (2 * j));
    {
      uint32_t A1[2][2][4], B2[4][2][2];
      float tw[2][4][2];
#pragma unroll
      for (int q = 0; q < 4; q++)
#pragma unroll
        for (int i = 0; i < 4; i++) {
          A1[q >> 1][q & 1][i] = ca[q][i];
          tw[q >> 1][2 * (q & 1) + (i >> 1)][i & 1] = __uint_as_float(ca[4 + q][i]);
          B2[q][i >> 1][i & 1] = ca[8 + q][i];
        }
      float T[2][2][2][4], s1[2], s2[2];
      row_stats(xr, s1, s2, lane);
      {
        uint32_t z[2][4][2];
#pragma unroll
        for (int u = 0; u < 2; u++)
#pragma unroll
          for (int i = 0; i < 4; i++) { z[u][i][0] = xr[u][i].x; z[u][i][1] = xr[u][i].y; }
        fft256a<true>(T, z, A1);
      }
      uint32_t pe[2][2][4];
#pragma unroll
      for (int u = 0; u < 2; u++) {
        const float mean = s1[u] * (1.f / D_);
        float rstd; asm("rsqrt.approx.ftz.f32 %0, %1;" : "=f"(rstd) : "f"(fmaxf(fmaf(-mean, mean, s2[u] * (1.f / D_)), 0.f) + 1e-5f));
        mean1[u] = mean;
        const float off = c ? 0.f : -4.f * mean * rstd;
#pragma unroll
        for (int uu = 0; uu < 2; uu++)
#pragma unroll
          for (int p = 0; p < 2; p++)
#pragma unroll
            for (int xx = 0; xx < 4; xx++) T[u][uu][p][xx] = xx < 2 ? fmaf(T[u][uu][p][xx], rstd, off) : T[u][uu][p][xx] * rstd;
      }
      float OO[2][4][4];
      fft256b<false>(OO, T, tw, B2);
#pragma unroll
      for (int u = 0; u < 2; u++) {
        const float (&O)[4][4] = OO[u];
        uint32_t qv[2], ov[2], tv[2];
#pragma unroll
        for (int g = 0; g < 2; g++) {
          qv[g] = pk<false>(O[2 * g + 1][0], O[2 * g + 1][1]);
          ov[g] = pk<false>(O[2 * g + 1][2], O[2 * g + 1][3]);
          tv[g] = __shfl_sync(~0u, qv[g], (lane & ~3) | ((lane - 1) & 3));
        }
#pragma unroll
        for (int g = 0; g < 2; g++) {
          pe[u][g][0] = pk<false>(O[2 * g][0], O[2 * g][1]);
          pe[u][g][1] = c ? ov[g] : (j ? tv[g] : tv[g ^ 1]);
          pe[u][g][2] = pk<false>(O[2 * g][2], O[2 * g][3]);
          pe[u][g][3] = c ? qv[g] : ov[g];
        }
      }
#pragma unroll
      for (int g = 0; g < 2; g++)
#pragma unroll
        for (int tau = 0; tau < 2; tau++)
          sts4(E0 + w * 2080 + tau * 1024 + (j + 4 * g) * 128 + ((c ^ (2 * j)) << 4), pe[0][g][2 * tau], pe[0][g][2 * tau + 1], pe[1][g][2 * tau], pe[1][g][2 * tau + 1]);
      bar_sync(1, 256);
      uint32_t L[2][2][4];
#pragma unroll
      for (int q = 0; q < 4; q++) lds4(L[q >> 1][q & 1], E0 + (4 * (q >> 1) + j) * 2080 + (q & 1) * 1024 + w * 128 + ((c ^ (2 * (w & 3))) << 4));
      float O2[2][4][4];
      stage_dataA<false>(O2, BC, L);
#pragma unroll
      for (int v = 0; v < 4; v++) {
        stg_relaxed4(&sc->z1[((4 * v + j) * 8 + w) * 1024 + b * 8 + (c ^ ((b >> 2) & 6))], (pk<false>(O2[0][v][0], O2[0][v][1]) & ~1u) | tag,
                     pk<false>(O2[0][v][2], O2[0][v][3]), pk<false>(O2[1][v][0], O2[1][v][1]), pk<false>(O2[1][v][2], O2[1][v][3]));
        if (v == 0 && tid < NREP) red_add(&sc->cnt[((b / (NCTA / NGRP)) * NREP + tid) * 32], 1);
      }
      if (tid == 0) sts1(bar + 8 * B_NUM, ep);
    }
    {
      float M[2][2][2][6];
      mbar_wait(bar + 8 * B_T, 0);
      {
        const int k1B = mblk, pgB = jF, k1m = (16 - k1B) & 15;
        const bool special = (pgB == 0 && c == 0);
        float wv[2][2][2][4], wsp[2][2][2];
#pragma unroll
        for (int y = 0; y < 2; y++)
#pragma unroll
          for (int v = 0; v < 2; v++) {
            const int ka = 2 * w + y + 16 * (4 * v + j), km = ((k1B ? 127 : 128) - ka) & 127;
            const uint32_t rs = sb + SM_W + ((2 * w + y) * 8 + 4 * v + j) * 16 + (k1B & 7) * 2;
            const uint32_t r1 = sb + SM_W + ((2 * w + y) * 8 + 4 * v + j) * 48, r2 = sb + SM_W + ((km & 15) * 8 + (km >> 4)) * 48;
#pragma unroll
            for (int tau = 0; tau < 2; tau++) {
              const int pl = rmap(tau, c);
              const uint32_t o1 = (tau == 0 && special) ? rs + 4 * 6144 : r1 + ((k1B & 7) + pl) * 2;
              const uint32_t o2 = r2 + 2 * 6144 + (((k1m + 1) & 7) + 15 - pl) * 2;
              wv[y][tau][v][0] = ldsw(o1); wv[y][tau][v][1] = ldsw(o1 + 6144);
              wv[y][tau][v][2] = ldsw(o2); wv[y][tau][v][3] = ldsw(o2 + 6144);
            }
            wsp[y][v][0] = ldsw(rs + 6 * 6144); wsp[y][v][1] = ldsw(rs + 7 * 6144);
          }
#pragma unroll
        for (int tau = 0; tau < 2; tau++) {
          float ct, st;
          cexp<512>(16 * pgB + rmap(tau, c), ct, st);
          if (tau == 0 && special) ct = 0.f;
          const float am = 0.5f - 0.5f * st, ap = 0.5f + 0.5f * st;
          ct *= 0.5f;
#pragma unroll
          for (int y = 0; y < 2; y++)
#pragma unroll
            for (int v = 0; v < 2; v++) {
              const float* q = wv[y][tau][v];
              float* m = M[y][tau][v];
              m[0] = am * q[0] + ap * q[2]; m[1] = am * q[1] - ap * q[3];
              m[2] = ap * q[0] + am * q[2]; m[3] = ap * q[1] - am * q[3];
              m[4] = ct * (q[0] - q[2]); m[5] = ct * (q[1] + q[3]);
              if (tau == 0 && special) { m[2] = wsp[y][v][0]; m[3] = wsp[y][v][1]; }
            }
        }
#pragma unroll
        for (int i = 0; i < 48; i++) asm volatile("" : "+f"((&M[0][0][0][0])[i]));
      }
      uint32_t AB[2][2][4], B8[4], B8i[4], BL[4][2][2];
      get_a(AB, sb + SM_CB + w * 4096, lane); get_b(BL, sb + SM_CB + w * 4096 + 2048, lane);
      lds4(B8, sb + SM_C8 + lane * 16); lds4(B8i, sb + SM_C8 + 512 + lane * 16);
      {
        float T[4][2][4];
        recv_stage<false>(T, AB, sb + SM_X + xo * 16, bar + 8 * B_X, &sc->z1[b * 1024 + xo], tag);
#pragma unroll
        for (int x = 0; x < 4; x++)
          sts4(E1 + w * 2080 + (c + 8 * (x >> 1)) * 128 + (((2 * j + (x & 1)) ^ (c & 1)) << 4), pk<false>(T[0][0][x], T[0][1][x]),
               pk<false>(T[1][0][x], T[1][1][x]), pk<false>(T[2][0][x], T[2][1][x]), pk<false>(T[3][0][x], T[3][1][x]));
      }
      bar_sync(1, 256);
      uint32_t LM[2][2][4];
#pragma unroll
      for (int y = 0; y < 2; y++) {
        lds4(LM[y][0], E1 + j * 2080 + (2 * w + y) * 128 + ((c ^ y) << 4));
        lds4(LM[y][1], E1 + (j + 4) * 2080 + (2 * w + y) * 128 + ((c ^ y) << 4));
      }
#pragma unroll
      for (int tau = 0; tau < 2; tau++) {
        float G[2][2][4];
#pragma unroll
        for (int y = 0; y < 2; y++) {
          uint32_t a[4];
#pragma unroll
          for (int v = 0; v < 2; v++) {
            float Y[4] = {0.f, 0.f, 0.f, 0.f};
            mma16816<false>(Y, LM[y][0][2 * tau], LM[y][0][2 * tau + 1], LM[y][1][2 * tau], LM[y][1][2 * tau + 1], B8[2 * v], B8[2 * v + 1]);
            const float* m = M[y][tau][v];
            const float ur = m[0] * Y[0] - m[1] * Y[1] - m[4] * Y[3] - m[5] * Y[2];
            const float ui = m[0] * Y[1] + m[1] * Y[0] + m[4] * Y[2] - m[5] * Y[3];
            const float vr = m[2] * Y[2] - m[3] * Y[3] + m[4] * Y[1] + m[5] * Y[0];
            const float vi = m[2] * Y[3] + m[3] * Y[2] - m[4] * Y[0] + m[5] * Y[1];
            a[2 * v] = pk<INV_BF>(ur, ui); a[2 * v + 1] = pk<INV_BF>(vr, vi);
          }
#pragma unroll
          for (int v = 0; v < 2; v++) {
#pragma unroll
            for (int x = 0; x < 4; x++) G[y][v][x] = 0.f;
            mma16816<INV_BF>(G[y][v], a[0], a[1], a[2], a[3], B8i[2 * v], B8i[2 * v + 1]);
          }
        }
#pragma unroll
        for (int v = 0; v < 2; v++)
          sts4(E0 + (4 * v + j) * 2080 + tau * 1024 + w * 128 + ((c ^ (2 * (w & 3))) << 4), pk<INV_BF>(G[0][v][0], G[0][v][1]),
               pk<INV_BF>(G[0][v][2], G[0][v][3]), pk<INV_BF>(G[1][v][0], G[1][v][1]), pk<INV_BF>(G[1][v][2], G[1][v][3]));
      }
      bar_sync(1, 256);
      uint32_t L[2][2][4];
#pragma unroll
      for (int q = 0; q < 4; q++) lds4(L[q >> 1][q & 1], E0 + w * 2080 + (q & 1) * 1024 + (4 * (q >> 1) + j) * 128 + ((c ^ (2 * j)) << 4));
      float O2[2][4][4];
      stage_dataA<INV_BF>(O2, BL, L);
#pragma unroll
      for (int v = 0; v < 4; v++) {
        stg_relaxed4(&sc->z2[(8 * (4 * v + j) + w) * 1024 + b * 8 + (c ^ ((b >> 2) & 6))], (pk<INV_BF>(O2[0][v][0], O2[0][v][1]) & ~1u) | tag,
                     pk<INV_BF>(O2[0][v][2], O2[0][v][3]), pk<INV_BF>(O2[1][v][0], O2[1][v][1]), pk<INV_BF>(O2[1][v][2], O2[1][v][3]));
        if (v == 0 && tid < NREP) red_add(&sc->cnt[(256 + (b / (NCTA / NGRP)) * NREP + tid) * 32], 1);
      }
    }
    {
      uint32_t AC[2][2][4], A1[2][2][4], B2[4][2][2];
      float tw[2][4][2];
      get_a(A1, sb + SM_CC, lane); get_tw(tw, sb + SM_CC + 2048, lane); get_b(B2, sb + SM_CC + 4096, lane); get_a(AC, sb + SM_AC, lane);
      {
        float T[4][2][4];
        recv_stage<INV_BF>(T, AC, sb + SM_X + xo * 16, bar + 8 * (B_X + 1), &sc->z2[b * 1024 + xo], tag);
#pragma unroll
        for (int x = 0; x < 4; x++)
          sts4(E1 + (c + 8 * (x >> 1)) * 1040 + w * 128 + (((2 * j + (x & 1)) ^ (2 * (w & 3))) << 4), pk<INV_BF>(T[0][0][x], T[0][1][x]),
               pk<INV_BF>(T[1][0][x], T[1][1][x]), pk<INV_BF>(T[2][0][x], T[2][1][x]), pk<INV_BF>(T[3][0][x], T[3][1][x]));
      }
      bar_sync(1, 256);
      uint32_t P[2][2][4];
#pragma unroll
      for (int u = 0; u < 2; u++)
#pragma unroll
        for (int g = 0; g < 2; g++) lds4(P[u][g], E1 + (2 * w + u) * 1040 + (j + 4 * g) * 128 + ((c ^ (2 * j)) << 4));
      float s1[2], s2[2];
      uint32_t zz[2][4][2];
#pragma unroll
      for (int u = 0; u < 2; u++) {
        uint32_t (&z)[4][2] = zz[u];
        uint32_t tv[2];
#pragma unroll
        for (int g = 0; g < 2; g++) tv[g] = __shfl_sync(~0u, P[u][g][1], (lane & ~3) | ((lane + 1) & 3));
#pragma unroll
        for (int g = 0; g < 2; g++) {
          z[2 * g][0] = P[u][g][0]; z[2 * g][1] = P[u][g][2];
          z[2 * g + 1][1] = c ? P[u][g][1] : P[u][g][3];
          z[2 * g + 1][0] = c ? P[u][g][3] : (j < 3 ? tv[g] : tv[g ^ 1]);
        }
      }
      float T2[2][2][2][4], OO[2][4][4];
      fft256a<INV_BF>(T2, zz, A1);
      uint32_t ta[2][2][4];
#pragma unroll
      for (int uu = 0; uu < 2; uu++)
#pragma unroll
        for (int u = 0; u < 2; u++)
#pragma unroll
          for (int x = 0; x < 4; x++)
            ta[u][uu][x] = pk<INV_BF>(T2[u][uu][0][x] * tw[uu][x][0] - T2[u][uu][1][x] * tw[uu][x][1], T2[u][uu][0][x] * tw[uu][x][1] + T2[u][uu][1][x] * tw[uu][x][0]);
#pragma unroll
      for (int part = 0; part < 2; part++) {
#pragma unroll
        for (int uu = 0; uu < 2; uu++)
#pragma unroll
          for (int v = 2 * part; v < 2 * part + 2; v++)
#pragma unroll
            for (int u = 0; u < 2; u++) {
              if (uu == 0) { OO[u][v][0] = OO[u][v][1] = OO[u][v][2] = OO[u][v][3] = 0.f; }
              mma16816<INV_BF>(OO[u][v], ta[u][uu][0], ta[u][uu][2], ta[u][uu][1], ta[u][uu][3], B2[v][uu][0], B2[v][uu][1]);
            }
#pragma unroll
        for (int v = 2 * part; v < 2 * part + 2; v++)
#pragma unroll
          for (int u = 0; u < 2; u++) {
            const uint32_t h0 = bf2_add(xr[u][v].x, pk<true>(OO[u][v][0], OO[u][v][1])), h1 = bf2_add(xr[u][v].y, pk<true>(OO[u][v][2], OO[u][v][3]));
            xr[u][v].x = h0; xr[u][v].y = h1;
            const uint32_t l0 = pk<true>(bf_lo(h0) - mean1[u], bf_hi(h0) - mean1[u]), l1 = pk<true>(bf_lo(h1) - mean1[u], bf_hi(h1) - mean1[u]);
            if (part == 0) asm volatile("st.global.v2.u32 [%0], {%1,%2};" ::"l"(sc->ln2 + (size_t)(b * 16 + 2 * w + u) * 256 + 128 * v + 32 * j + 4 * c), "r"(l0), "r"(l1) : "memory");
            else asm volatile("st.shared.v2.u32 [%0], {%1,%2};" ::"r"(sb + SM_X + (2 * w + u) * 512 + (v - 2) * 256 + 64 * j + 8 * c), "r"(l0), "r"(l1) : "memory");
          }
        if (part == 0) { __syncwarp(); if (lane == 0) mbar_arrive(bar + 8 * B_L0); mbar_wait(bar + 8 * B_T, 0); }
      }
      row_stats(xr, s1, s2, lane);
      {
        const float m = (lane ? s1[1] : s1[0]) * (1.f / D_);
        const float var = fmaxf(fmaf(-m, m, (lane ? s2[1] : s2[0]) * (1.f / D_)), 0.f);
        float inv; asm("rsqrt.approx.ftz.f32 %0, %1;" : "=f"(inv) : "f"(var + 1e-5f));
        if (lane < 2) sts1(bar + 384 + (2 * w + lane) * 4, __float_as_uint(inv));
      }
      asm volatile("fence.proxy.async.shared::cta;" ::: "memory");
      __syncwarp();
      if (lane == 0) mbar_arrive(bar + 8 * B_LN);
    }
    const int wg = warp >> 2;
    const uint32_t descA0 = mkdesc(sb + SM_A + wg * 8192, 16);
    const uint32_t descB0 = pin32(mkdesc(sb + SM_RING, 4096));
    uint32_t act[28][4];
    int slot = 0; uint32_t ph = 0;
    asm volatile("barrier.cluster.wait.acquire.aligned;" ::: "memory");
    mbar_wait(bar + 8 * B_FULL, 0);

    const uint32_t peerA = mapa(sb + SM_A + warp * 2048, e_ ^ 1);
    const uint32_t peerBar = mapa(bar, e_ ^ 1);
    uint32_t up[4][4];
    float rs[2] = {0.f, 0.f};
    {
      float acc[112];
      uint32_t da = descA0;
      const float* rsp = &sc->rstd[mblk * 128 + warp * 16 + c];
      asm volatile("" : "+l"(rsp));
      mbar_wait(bar + 8 * B_AFULL, 0);
#pragma unroll 1
      for (int st = 0; st < 16; st++) {
        const uint32_t db = descB0 + slot * (SLOT_BYTES >> 4);
        wg_fence();
        wgmma_ss_n224(acc, da, db, st);
        wgmma_ss_n224(acc, da + 2, db + 128, 1);
        wg_commit();
        da += (st & 1) ? 1020 : 4;
        const uint32_t rel = bar + 8 * (B_EMPTY + (slot == 0 ? NSLOT - 1 : slot - 1));
        if (++slot == NSLOT) { slot = 0; ph ^= 1; }
        if (st == 4) bar_arrive(9, 288);
        if (st == 12) {
#pragma unroll
          for (int i = 0; i < 2; i++) rs[i] = __uint_as_float(ld_relaxed(reinterpret_cast<const unsigned*>(rsp + 8 * i)));
        }
        if ((st & 1) && st < 15) mbar_wait(bar + 8 * (B_AFULL + ((st + 1) >> 1)), 0);
        mbar_wait(bar + 8 * (B_FULL + slot), ph);
        wg_wait<1>();
        if (st > 0 && lane == 0) mbar_arrive(rel);
      }
      wg_wait<0>();
      reg_fence(acc);
      if (lane == 0) mbar_arrive(bar + 8 * (B_EMPTY + 15 % NSLOT));
#pragma unroll
      for (int kk = 0; kk < 6; kk++)
#pragma unroll
        for (int x = 0; x < 4; x++) {
          if (kk < 4) {
            act[kk][x] = pk<true>(acc[8 * kk + 2 * x], acc[8 * kk + 2 * x + 1]);
            up[kk][x] = pk<true>(acc[32 + 8 * kk + 2 * x], acc[32 + 8 * kk + 2 * x + 1]);
          }
          act[8 + kk][x] = pk<true>(acc[64 + 8 * kk + 2 * x], acc[64 + 8 * kk + 2 * x + 1]);
        }
#pragma unroll
      for (int st = 0; st < 16; st++) {
        const uint32_t db = descB0 + slot * (SLOT_BYTES >> 4);
        if (++slot == NSLOT) slot = 0;
        wg_fence();
        wgmma_ss_n224(acc, descA0 + (st >> 1) * 1024 + (st & 1) * 4, db, st);
        wgmma_ss_n224(acc, descA0 + (st >> 1) * 1024 + (st & 1) * 4 + 2, db + 128, 1);
        wg_commit();
#pragma unroll
        for (int q = 3 * st; q < 3 * st + 3 && q < 40; q++) {
          const int i = q >> 2, x = q & 3;
          uint32_t& r = act[i < 4 ? i : 4 + i][x];
          asm volatile("" : "+r"(r));
          r = silu2(r, rs[x & 1]);
          if (i < 4) r = bf2_mul(r, up[i][x]);
          asm volatile("" : "+r"(r));
        }
        if (st < 8) *reinterpret_cast<uint2*>(sc->h + (size_t)(b * 16 + 2 * w + (st >> 2)) * D_ + 32 * j + 4 * c + 128 * (st & 3)) = xr[st >> 2][st & 3];
        if (st == 7) bar_arrive(10, 288);
        if (st == 9 && lane == 0) mbar_arrive_remote(peerBar + 8 * (B_PFREE + wg));
        if (st == 11) mbar_wait_cluster(bar + 8 * (B_PFREE + wg), 0);
        if (st >= 11 && st < 15) st_async4(peerA + (st - 11) * 512 + lane * 16, act[st - 11], peerBar + 8 * (B_ACT + 3 * wg));
        mbar_wait(bar + 8 * (B_FULL + (17 + st) % NSLOT), ((17 + st) / NSLOT) & 1);
        wg_wait<1>();
        if (st > 0 && lane == 0) mbar_arrive(bar + 8 * (B_EMPTY + (15 + st) % NSLOT));
      }
      wg_wait<0>();
      reg_fence(acc);
      if (lane == 0) mbar_arrive(bar + 8 * (B_EMPTY + 31 % NSLOT));
      bar_arrive(5, 288);
#pragma unroll
      for (int kk = 0; kk < 6; kk++) {
#pragma unroll
        for (int x = 0; x < 4; x++) act[8 + kk][x] = bf2_mul(act[8 + kk][x], pk<true>(acc[64 + 8 * kk + 2 * x], acc[64 + 8 * kk + 2 * x + 1]));
        if (kk < 3) st_async4(peerA + lane * 16 + 16384 + kk * 512, act[8 + kk], peerBar + 8 * (B_ACT + 3 * wg + 1));
      }
#pragma unroll
      for (int kk = 0; kk < 4; kk++)
#pragma unroll
        for (int x = 0; x < 4; x++) {
          act[14 + kk][x] = pk<true>(acc[8 * kk + 2 * x], acc[8 * kk + 2 * x + 1]);
          up[kk][x] = pk<true>(acc[32 + 8 * kk + 2 * x], acc[32 + 8 * kk + 2 * x + 1]);
        }
    }
    {
      float acc[2][32];
      uint32_t ph_[4][4], pu[4][4], pv[4][4];
      const uint32_t myA = sb + SM_A + warp * 2048 + lane * 16;
      const uint4* psrc = &sc->part[b * 3 * 1024 + warp * 128 + lane];
      const uint32_t ident = (c == 2 * j) ? 0x00003f80u : ((c == 2 * j + 1) ? 0x3f800000u : 0u);
      const uint32_t ht = sb + SM_A + 7 * 16384 + warp * 2048 + ((lane & 7) + ((lane >> 3) & 1) * 8) * 128;
      auto ship = [&](int tp) {
        float (&pa)[32] = acc[tp & 1];
        reg_fence(pa);
        const uint32_t stg = sb + SM_A + tp * 16384 + warp * 2048;
#pragma unroll
        for (int i = 0; i < 4; i++)
          sts4(stg + i * 512 + lane * 16, (pk<true>(pa[8 * i], pa[8 * i + 1]) & ~1u) | (tp == 2 ? 1u : tag), pk<true>(pa[8 * i + 2], pa[8 * i + 3]),
               pk<true>(pa[8 * i + 4], pa[8 * i + 5]), pk<true>(pa[8 * i + 6], pa[8 * i + 7]));
        asm volatile("fence.proxy.async.shared::cta;" ::: "memory");
        __syncwarp();
        if (elect_one())
          asm volatile("cp.async.bulk.global.shared::cta.bulk_group [%0], [%1], 2048;"
                       ::"l"(&sc->part[((mblk * 8 + ((r4 + 1 + tp) & 3) * 2 + e_) * 3 + tp) * 1024 + warp * 128]), "r"(stg) : "memory");
      };
      auto fetch = [&](int tp) {
#pragma unroll
        for (int i = 0; i < 4; i++)
          asm volatile("cp.async.cg.shared.global [%0], [%1], 16;" ::"r"(myA + (4 + tp) * 16384 + i * 512), "l"(psrc + tp * 1024 + i * 32) : "memory");
        asm volatile("cp.async.commit_group;" ::: "memory");
      };
      auto pick = [&](uint32_t (&p)[4][4], int tp) {
#pragma unroll
        for (int i = 0; i < 4; i++) lds4(p[i], myA + (4 + tp) * 16384 + i * 512);
        check_tagged(p, psrc + tp * 1024, 32, tp == 2 ? 1u : tag);
      };
      auto addp = [&](const uint32_t (&p)[4][4]) {
#pragma unroll
        for (int i = 0; i < 4; i++) {
#pragma unroll
          for (int q = 0; q < 2; q++)
            asm volatile("mma.sync.aligned.m16n8k8.row.col.f32.bf16.bf16.f32 {%0,%1,%2,%3}, {%4,%5}, {%6}, {%0,%1,%2,%3};"
                         : "+f"(acc[1][8 * i + 4 * q]), "+f"(acc[1][8 * i + 4 * q + 1]), "+f"(acc[1][8 * i + 4 * q + 2]), "+f"(acc[1][8 * i + 4 * q + 3])
                         : "r"(p[i][2 * q]), "r"(p[i][2 * q + 1]), "r"(ident));
        }
      };
#pragma unroll
      for (int n = 0; n < 16; n++) {
        const int t = (G2_T >> (2 * n)) & 3, qq = (G2_Q >> (2 * n)) & 3;
        const int pr = (31 + n) % NSLOT;
        const int k0 = 14 * (qq >> 1) + 8 * (qq & 1), nk = (qq & 1) ? 6 : 8;
        if (n == 0) {
          mbar_wait_cluster(bar + 8 * (B_ACT + 3 * wg), 0);
#pragma unroll
          for (int kk = 0; kk < 4; kk++) lds4(act[4 + kk], myA + kk * 512);
        }
        const uint32_t db = descB0 + slot * (SLOT_BYTES >> 4);
        if (++slot == NSLOT) slot = 0;
        wg_fence();
#pragma unroll
        for (int kk = 0; kk < nk; kk++)
          wgmma_rs_n64(acc[t & 1], act[k0 + kk], db + kk * 128, (qq | kk) != 0);
        wg_commit();
        if (n < 3) {
          const uint32_t pa = peerA + lane * 16;
          if (n == 0) st_async4(pa + 16384 + 3 * 512, act[11], peerBar + 8 * (B_ACT + 3 * wg + 1));
          if (n == 1) {
            st_async4(pa + 3 * 16384, act[12], peerBar + 8 * (B_ACT + 3 * wg + 2));
            st_async4(pa + 3 * 16384 + 512, act[13], peerBar + 8 * (B_ACT + 3 * wg + 2));
          }
#pragma unroll
          for (int kk = (3 * n) / 2; kk < (3 * n + 3) / 2; kk++) {
#pragma unroll
            for (int x = 0; x < 4; x++) {
              asm volatile("" : "+r"(act[14 + kk][x]));
              act[14 + kk][x] = bf2_mul(silu2(act[14 + kk][x], rs[x & 1]), up[kk][x]);
              asm volatile("" : "+r"(act[14 + kk][x]));
            }
            st_async4(pa + 2 * 16384 + kk * 512, act[14 + kk], peerBar + 8 * (B_ACT + 3 * wg + 2));
          }
        }
        if (n == 3 || n == 4) {
          const int g = (n == 3) ? 1 : 2;
          mbar_wait_cluster(bar + 8 * (B_ACT + 3 * wg + g), 0);
#pragma unroll
          for (int kk = 0; kk < (g == 2 ? 6 : 4); kk++) lds4(act[(g == 1 ? 18 : 22) + kk], myA + (g + (kk >> 2)) * 16384 + (kk & 3) * 512);
        }
        if (n == 11) mbar_wait(bar + 8 * B_RS, 0);
        if (n == 9) ship(1);
        if (n == 13) { fetch(0); fetch(1); }
        if (n == 14) {
          mbar_wait(bar + 8 * (B_PART + wg), 0);
#pragma unroll
          for (int i = 0; i < 4; i++)
            asm volatile("ldmatrix.sync.aligned.m8n8.x4.shared.b16 {%0,%1,%2,%3}, [%4];" : "=r"(ph_[i][0]), "=r"(ph_[i][1]), "=r"(ph_[i][2]), "=r"(ph_[i][3])
                         : "r"(ht + (((2 * i + (lane >> 4)) ^ (lane & 7)) << 4)) : "memory");
        }
        if (n < 15) mbar_wait(bar + 8 * (B_FULL + (33 + n) % NSLOT), ((33 + n) / NSLOT) & 1);
        if (n > 0 && n < 13) { wg_wait<1>(); if (n < 11 && lane == 0) mbar_arrive(bar + 8 * (B_EMPTY + pr)); }
        if (n == 6) ship(0);
        if (n == 12) ship(2);
      }
      fetch(2);
      asm volatile("cp.async.wait_group 1;" ::: "memory");
#pragma unroll
      for (int i = 0; i < 4; i++) { lds4(pu[i], myA + 4 * 16384 + i * 512); lds4(pv[i], myA + 5 * 16384 + i * 512); }
      check_tagged(pu, psrc, 32, tag);
      check_tagged(pv, psrc + 1024, 32, tag);
      wg_wait<0>();
      reg_fence(acc[1]);
      addp(ph_); addp(pu); addp(pv);
      asm volatile("cp.async.wait_group 0;" ::: "memory");
      pick(pu, 2);
      addp(pu);
#pragma unroll
      for (int i = 0; i < 4; i++)
        asm volatile("stmatrix.sync.aligned.m8n8.x4.shared.b16 [%0], {%1,%2,%3,%4};" ::"r"(ht + (((2 * i + (lane >> 4)) ^ (lane & 7)) << 4)),
                     "r"(pk<true>(acc[1][8 * i], acc[1][8 * i + 1])), "r"(pk<true>(acc[1][8 * i + 2], acc[1][8 * i + 3])),
                     "r"(pk<true>(acc[1][8 * i + 4], acc[1][8 * i + 5])), "r"(pk<true>(acc[1][8 * i + 6], acc[1][8 * i + 7])) : "memory");
      __syncwarp();
#pragma unroll
      for (int i = 0; i < 4; i++) {
        const int row = 4 * i + (lane >> 3);
        lds4(pv[i], sb + SM_A + 7 * 16384 + warp * 2048 + row * 128 + (((lane & 7) ^ (row & 7)) << 4));
      }
#pragma unroll
      for (int i = 0; i < 4; i++)
        *reinterpret_cast<uint4*>(out + (size_t)(128 * (4 * i + (lane >> 3)) + mblk * 8 + warp) * D_ + e_ * 256 + r4 * 64 + (lane & 7) * 8) = make_uint4(pv[i][0], pv[i][1], pv[i][2], pv[i][3]);
      if (elect_one()) {
        asm volatile("cp.async.bulk.commit_group;" ::: "memory");
        asm volatile("cp.async.bulk.wait_group.read 0;" ::: "memory");
      }
    }
  }
}


__device__ float g_fa[S_ * D_];
__device__ float2 g_fx[S_ * WCOLS], g_fy[S_ * WCOLS];
__device__ float g_fact[S_ * F_];
__device__ __forceinline__ float rb(float v) { return __bfloat162float(__float2bfloat16(v)); }
__global__ void fb_ln(const __nv_bfloat16* x) {
  __shared__ float red[512];
  const int s = blockIdx.x, t = threadIdx.x;
  const float v = __bfloat162float(x[s * D_ + t]);
  red[t] = v; __syncthreads();
  for (int o = 256; o > 0; o >>= 1) { if (t < o) red[t] += red[t + o]; __syncthreads(); }
  const float mean = red[0] / D_; __syncthreads();
  red[t] = (v - mean) * (v - mean); __syncthreads();
  for (int o = 256; o > 0; o >>= 1) { if (t < o) red[t] += red[t + o]; __syncthreads(); }
  g_fa[s * D_ + t] = rb(rb(v - rb(mean)) / rb(sqrtf(rb(rb(red[0] / D_) + 1e-5f))));
}
__global__ void fb_rowdft() {
  const int s = blockIdx.x, k = threadIdx.x;
  if (k >= WCOLS) return;
  float re = 0.f, im = 0.f;
  for (int d = 0; d < D_; d++) { float si, co; sincospif(-2.f * ((d * k) & 511) / 512.f, &si, &co); re += g_fa[s * D_ + d] * co; im += g_fa[s * D_ + d] * si; }
  g_fx[s * WCOLS + k] = make_float2(re, im);
}
__global__ void fb_coldft(int inverse, const __nv_bfloat16* wr, const __nv_bfloat16* wi) {
  __shared__ float2 tw[S_];
  for (int i = threadIdx.x; i < S_; i += blockDim.x) sincospif((inverse ? 2.f : -2.f) * i / S_, &tw[i].y, &tw[i].x);
  __syncthreads();
  const int sp = blockIdx.x, k = threadIdx.x;
  if (k >= WCOLS) return;
  const float2* X = inverse ? g_fy : g_fx;
  float re = 0.f, im = 0.f;
  for (int s = 0; s < S_; s++) { const float2 w = tw[(s * sp) & (S_ - 1)], v = X[s * WCOLS + k]; re += v.x * w.x - v.y * w.y; im += v.x * w.y + v.y * w.x; }
  if (inverse) g_fx[sp * WCOLS + k] = make_float2(re, im);
  else {
    const float a = __bfloat162float(wr[sp * WCOLS + k]), b = __bfloat162float(wi[sp * WCOLS + k]);
    g_fy[sp * WCOLS + k] = make_float2(re * a - im * b, re * b + im * a);
  }
}
__global__ void fb_rowidft(const __nv_bfloat16* x, __nv_bfloat16* h) {
  const int s = blockIdx.x, d = threadIdx.x;
  float acc = g_fx[s * WCOLS].x + g_fx[s * WCOLS + 256].x * ((d & 1) ? -1.f : 1.f);
  for (int k = 1; k < 256; k++) { float si, co; sincospif(2.f * ((d * k) & 511) / 512.f, &si, &co); acc += 2.f * (g_fx[s * WCOLS + k].x * co - g_fx[s * WCOLS + k].y * si); }
  h[s * D_ + d] = __float2bfloat16(__bfloat162float(x[s * D_ + d]) + rb(acc * (1.f / (S_ * D_))));
}
__global__ void fb_ffn1(const __nv_bfloat16* wg, const __nv_bfloat16* wu) {
  __shared__ float row[D_];
  const int s = blockIdx.x;
  for (int i = threadIdx.x; i < D_; i += blockDim.x) row[i] = g_fa[s * D_ + i];
  __syncthreads();
  for (int f = threadIdx.x; f < F_; f += blockDim.x) {
    float g = 0.f, u = 0.f;
    for (int d = 0; d < D_; d++) { g += row[d] * __bfloat162float(wg[d * F_ + f]); u += row[d] * __bfloat162float(wu[d * F_ + f]); }
    g = rb(g);
    g_fact[s * F_ + f] = rb(rb(g / (1.f + expf(-g))) * rb(u));
  }
}
__global__ void fb_ffn2(const __nv_bfloat16* wd, __nv_bfloat16* out) {
  __shared__ float row[F_];
  const int s = blockIdx.x, d = threadIdx.x;
  for (int i = threadIdx.x; i < F_; i += blockDim.x) row[i] = g_fact[s * F_ + i];
  __syncthreads();
  float o = 0.f;
  for (int f = 0; f < F_; f++) o += row[f] * __bfloat162float(wd[f * D_ + d]);
  out[s * D_ + d] = __float2bfloat16(__bfloat162float(out[s * D_ + d]) + rb(o));
}

typedef CUresult (*EncFn)(CUtensorMap*, CUtensorMapDataType, cuuint32_t, void*, const cuuint64_t*, const cuuint64_t*, const cuuint32_t*,
                          const cuuint32_t*, CUtensorMapInterleave, CUtensorMapSwizzle, CUtensorMapL2promotion, CUtensorMapFloatOOBfill);

void enc(EncFn f, CUtensorMap* m, int rank, const void* base, const cuuint64_t* dims, const cuuint64_t* strides, const cuuint32_t* box, CUtensorMapSwizzle sw) {
  cuuint32_t es[3] = {1, 1, 1};
  f(m, CU_TENSOR_MAP_DATA_TYPE_BFLOAT16, rank, const_cast<void*>(base), dims, strides, box, es, CU_TENSOR_MAP_INTERLEAVE_NONE, sw,
    CU_TENSOR_MAP_L2_PROMOTION_L2_128B, CU_TENSOR_MAP_FLOAT_OOB_FILL_NONE);
}

}

extern "C" void kernel_launch(void* const* d_in, const int* in_sizes, int n_in, void* d_out, int out_size) {
  (void)in_sizes; (void)n_in; (void)out_size;
  static EncFn f = nullptr;
  static void *p_s = nullptr, *p_t = nullptr;
  static bool resident = false;
  if (!f) {
    void* fn = nullptr; cudaDriverEntryPointQueryResult qr;
    cudaGetDriverEntryPoint("cuTensorMapEncodeTiled", &fn, cudaEnableDefault, &qr);
    f = (EncFn)fn;
    cudaFuncSetAttribute(fused_kernel, cudaFuncAttributeMaxDynamicSharedMemorySize, SMEM_BYTES);
    cudaGetSymbolAddress(&p_s, g_s);
    cudaGetSymbolAddress(&p_t, g_table);
    cudaLaunchConfig_t cfg = {};
    cfg.gridDim = dim3(NCTA); cfg.blockDim = dim3(384); cfg.dynamicSmemBytes = SMEM_BYTES;
    cudaLaunchAttribute at; at.id = cudaLaunchAttributeClusterDimension; at.val.clusterDim.x = 2; at.val.clusterDim.y = 1; at.val.clusterDim.z = 1;
    cfg.attrs = &at; cfg.numAttrs = 1;
    int ncl = 0;
    resident = cudaOccupancyMaxActiveClusters(&ncl, fused_kernel, &cfg) == cudaSuccess && ncl >= NCTA / 2;
  }
  if (!resident) {
    typedef const __nv_bfloat16* bp;
    __nv_bfloat16* o = (__nv_bfloat16*)d_out;
    fb_ln<<<S_, 512>>>((bp)d_in[0]);
    fb_rowdft<<<S_, 288>>>();
    fb_coldft<<<S_, 288>>>(0, (bp)d_in[1], (bp)d_in[2]);
    fb_coldft<<<S_, 288>>>(1, nullptr, nullptr);
    fb_rowidft<<<S_, 512>>>((bp)d_in[0], o);
    fb_ln<<<S_, 512>>>(o);
    fb_ffn1<<<S_, 256>>>((bp)d_in[4], (bp)d_in[5]);
    fb_ffn2<<<S_, 512>>>((bp)d_in[6], o);
    return;
  }
  Maps maps;
  {
    cuuint64_t d2[2] = {F_, D_}, s2[1] = {F_ * 2};
    cuuint32_t b64[2] = {64, 32}, b32[2] = {32, 32}, bq[2] = {64, 64};
    enc(f, &maps.gu[0], 2, d_in[4], d2, s2, b64, CU_TENSOR_MAP_SWIZZLE_128B);
    enc(f, &maps.gu[1], 2, d_in[5], d2, s2, b64, CU_TENSOR_MAP_SWIZZLE_128B);
    enc(f, &maps.gu[2], 2, d_in[4], d2, s2, b32, CU_TENSOR_MAP_SWIZZLE_128B);
    enc(f, &maps.gu[3], 2, d_in[5], d2, s2, b32, CU_TENSOR_MAP_SWIZZLE_128B);
    cuuint64_t dd[2] = {D_, F_}, sd[1] = {D_ * 2};
    enc(f, &maps.dn[0], 2, d_in[6], dd, sd, bq, CU_TENSOR_MAP_SWIZZLE_128B);
    enc(f, &maps.dn[1], 2, d_in[6], dd, sd, b64, CU_TENSOR_MAP_SWIZZLE_128B);
    cuuint64_t da[2] = {D_, S_};
    cuuint32_t bh[2] = {64, 64};
    cuuint64_t da0[2] = {128 * SV, S_}, sa0[1] = {256 * SV}, da1[2] = {512 - 128 * SV, S_}, sa1[1] = {1024 - 256 * SV};
    enc(f, &maps.a[0], 2, ((Scratch*)p_s)->ln2, da0, sa0, bh, CU_TENSOR_MAP_SWIZZLE_128B);
    enc(f, &maps.a[1], 2, ((Scratch*)p_s)->ln2 + S_ * 128 * SV, da1, sa1, bh, CU_TENSOR_MAP_SWIZZLE_128B);
    enc(f, &maps.h, 2, ((Scratch*)p_s)->h, da, sd, bh, CU_TENSOR_MAP_SWIZZLE_128B);
    cuuint64_t dW[3] = {16 * WCOLS, 8, 16}, sW[2] = {256 * WCOLS * 2, 16 * WCOLS * 2};
    cuuint32_t bW[3] = {24, 8, 16}, bW8[3] = {8, 8, 16};
    enc(f, &maps.w[0], 3, d_in[1], dW, sW, bW, CU_TENSOR_MAP_SWIZZLE_NONE);
    enc(f, &maps.w[1], 3, d_in[2], dW, sW, bW, CU_TENSOR_MAP_SWIZZLE_NONE);
    enc(f, &maps.w[2], 3, d_in[1], dW, sW, bW8, CU_TENSOR_MAP_SWIZZLE_NONE);
    enc(f, &maps.w[3], 3, d_in[2], dW, sW, bW8, CU_TENSOR_MAP_SWIZZLE_NONE);
  }
  fused_kernel<<<NCTA, 384, SMEM_BYTES>>>((const __nv_bfloat16*)d_in[0], (Scratch*)p_s, (const uint32_t*)p_t, (const char*)d_in[6], (__nv_bfloat16*)d_out, maps);
}
```
